```python
import torch

def _softmax(x, axis=-1):
    return torch.softmax(x, dim=axis)

def _gelu(x):
    return torch.nn.functional.gelu(x, approximate='tanh')

def _silu(x):
    return torch.nn.functional.silu(x)

def _sigmoid(x):
    return torch.sigmoid(x)

def _layernorm(x, axis=-1, eps=1e-05):
    m = x.mean(dim=axis, keepdim=True)
    v = x.var(dim=axis, keepdim=True, unbiased=False)
    return (x - m) / torch.sqrt(v + eps)

def _scatter_add(tgt, idx, src, axis=0):
    return tgt.clone().index_add_(axis, idx, src)

def _segment_sum(src, seg, n):
    out = torch.zeros((n,) + src.shape[1:], dtype=src.dtype)
    return out.index_add_(0, seg, src)

def _pad(x, pw):
    flat = tuple((v for pair in reversed(pw) for v in pair))
    return torch.nn.functional.pad(x, flat)
kernel_name = 'adaLN_cond__memory_aug_recurrent_mem_tr__geglu_ffn__prompt'

def setup_inputs():

    _w = lambda a: (lambda t: t.to(torch.bfloat16) if t.is_floating_point() else t)(torch.as_tensor(a))

    def _A_setup():
        B, S, Dm = (1, 2048, 640)
        H, Dh = (32, 128)
        M, seg = (8, 32)
        seg = min(seg, S)
        S = S // seg * seg
        return {'x': _w((lambda *s: torch.randn(*s, dtype=torch.bfloat16) * 0.05)(B, S, Dm)), 'mem0': _w((lambda *s: torch.randn(*s, dtype=torch.bfloat16) * 0.4)(B, M, Dm)), 'Wq': _w((lambda *s: torch.randn(*s, dtype=torch.bfloat16) * 3.2)(Dm, H, Dh) * Dm ** (-0.5)), 'Wk': _w((lambda *s: torch.randn(*s, dtype=torch.bfloat16) * 3.2)(Dm, H, Dh) * Dm ** (-0.5)), 'Wv': _w((lambda *s: torch.randn(*s, dtype=torch.bfloat16) * 0.4)(Dm, H, Dh) * Dm ** (-0.5)), 'Wo': _w((lambda *s: torch.randn(*s, dtype=torch.bfloat16) * 0.4)(H, Dh, Dm) * (H * Dh) ** (-0.5)), 'seg_len': seg}
    _A_in = _A_setup()

    def _B_setup():
        B, S, D, F = (1, 2048, 640, 1728)
        return {'x': _w((lambda *s: torch.randn(*s, dtype=torch.bfloat16) * 0.05)(B, S, D)), 'w_gate': _w((lambda *s: torch.randn(*s, dtype=torch.bfloat16) * 0.05)(D, F)), 'w_up': _w((lambda *s: torch.randn(*s, dtype=torch.bfloat16) * 0.05)(D, F)), 'w_down': _w((lambda *s: torch.randn(*s, dtype=torch.bfloat16) * 0.05)(F, D))}
    _B_in = _B_setup()
    return {'A_x': _A_in['x'], 'A_mem0': _A_in['mem0'], 'A_Wq': _A_in['Wq'], 'A_Wk': _A_in['Wk'], 'A_Wv': _A_in['Wv'], 'A_Wo': _A_in['Wo'], 'A_seg_len': _A_in['seg_len'], 'B_x': _B_in['x'], 'B_w_gate': _B_in['w_gate'], 'B_w_up': _B_in['w_up'], 'B_w_down': _B_in['w_down'], 'c': _w((lambda *s: torch.randn(*s, dtype=torch.bfloat16) * 0.1)(1, 640) * 8.0), 'w_mod': _w((lambda *s: torch.randn(*s, dtype=torch.bfloat16) * 0.1)(640, 6 * 640) * 640 ** (-0.5) * 8.0)}

def reference(A_x, A_mem0, A_Wq, A_Wk, A_Wv, A_Wo, A_seg_len, B_x, B_w_gate, B_w_up, B_w_down, c, w_mod):

    def _A_ref(x, mem0, Wq, Wk, Wv, Wo, seg_len):
        B, S, Dm = x.shape
        H, Dh = (Wq.shape[1], Wq.shape[2])
        M = mem0.shape[1]
        scale = Dh ** (-0.5)
        n_seg = S // seg_len
        L = M + seg_len
        idx = torch.arange(L)
        mask = (idx[:, None] < M) | (idx[:, None] >= idx[None, :])
        mem = mem0
        outs = []
        for s in range(n_seg):
            xs = x[:, s * seg_len:(s + 1) * seg_len, :].clone()
            h = torch.concatenate([mem, xs], axis=1)
            q = torch.einsum('btd,dhe->bhte', h, Wq)
            k = torch.einsum('btd,dhe->bhte', h, Wk)
            v = torch.einsum('btd,dhe->bhte', h, Wv)
            scores = torch.einsum('bhqe,bhke->bhqk', q, k) * scale
            scores = torch.where(mask[None, None], scores, -1000000000.0)
            p = _softmax(scores, axis=-1)
            o = torch.einsum('bhqk,bhke->bhqe', p, v)
            o = torch.einsum('bhte,hed->btd', o, Wo)
            mem = o[:, :M, :].clone()
            outs.append(o[:, M:, :])
        return torch.concatenate(outs, axis=1)

    def _B_ref(x, w_gate, w_up, w_down):
        return _gelu(x @ w_gate) * (x @ w_up) @ w_down
    x = A_x
    mod = (_silu(c) @ w_mod).reshape(c.shape[0], 6, 1, -1)
    sa, ca, ga, sb, cb, gb = (mod[:, 0].clone(), mod[:, 1].clone(), mod[:, 2].clone(), mod[:, 3].clone(), mod[:, 4].clone(), mod[:, 5].clone())
    h = _layernorm(x, axis=-1) * (1 + ca) + sa
    x = x + ga * _A_ref(h, A_mem0, A_Wq, A_Wk, A_Wv, A_Wo, A_seg_len)
    h = _layernorm(x, axis=-1) * (1 + cb) + sb
    x = x + gb * _B_ref(h, B_w_gate, B_w_up, B_w_down)
    return x
```

```cpp
#include <cuda_runtime.h>
#include <cuda_bf16.h>
#include <cuda.h>
#include <stdint.h>

typedef __nv_bfloat16 bf16;

constexpr int S_TOK = 2048, DM = 640, NH = 32, DH = 128, NMEM = 8, SEG = 32, NSEG = 64, FF = 1728;
constexpr int HD = NH * DH;

__device__ float g_mod[6 * DM];
__device__ __align__(1024) bf16 g_h[S_TOK * DM];
__device__ __align__(1024) bf16 g_q[NH * S_TOK * DH];
__device__ __align__(1024) bf16 g_k[NH * S_TOK * DH];
__device__ __align__(1024) bf16 g_v[NH * S_TOK * DH];
__device__ __align__(1024) bf16 g_km[NSEG * NH * NMEM * DH];
__device__ __align__(1024) bf16 g_vm[NSEG * NH * NMEM * DH];
__device__ __align__(1024) bf16 g_o[S_TOK * HD];
__device__ __align__(1024) bf16 g_x1[S_TOK * DM];
__device__ __align__(1024) bf16 g_h2[S_TOK * DM];
__device__ __align__(1024) bf16 g_act[S_TOK * FF];
__device__ __align__(1024) float g_part[2 * 40 * 8 * 32 * 16];
__device__ __align__(1024) uint32_t g_memb[4 * 2560];
__device__ int g_err;
__device__ unsigned g_kvflag[16 * 48];
__device__ unsigned g_resident;

__device__ __forceinline__ uint32_t smem_u32(const void* p) { return (uint32_t)__cvta_generic_to_shared(p); }
__device__ __forceinline__ uint32_t pack2(float lo, float hi) {
  uint32_t r; asm("cvt.rn.bf16x2.f32 %0, %1, %2;" : "=r"(r) : "f"(hi), "f"(lo)); return r;
}
__device__ __forceinline__ float bfr(float x) { return __uint_as_float(pack2(0.f, x) & 0xffff0000u); }
__device__ __forceinline__ float lo2f(uint32_t v) { return __uint_as_float(v << 16); }
__device__ __forceinline__ float hi2f(uint32_t v) { return __uint_as_float(v & 0xffff0000u); }

__device__ __forceinline__ void mbar_init(uint32_t bar, uint32_t cnt) {
  asm volatile("mbarrier.init.shared::cta.b64 [%0], %1;" ::"r"(bar), "r"(cnt) : "memory");
}
__device__ __forceinline__ void mbar_expect_tx(uint32_t bar, uint32_t bytes) {
  asm volatile("mbarrier.arrive.expect_tx.shared::cta.b64 _, [%0], %1;" ::"r"(bar), "r"(bytes) : "memory");
}
__device__ __forceinline__ void mbar_arrive(uint32_t bar) {
  asm volatile("mbarrier.arrive.shared::cta.b64 _, [%0];" ::"r"(bar) : "memory");
}
__device__ __forceinline__ bool mbar_try(uint32_t bar, uint32_t parity) {
  uint32_t ok;
  asm volatile("{\n.reg .pred p;\nmbarrier.try_wait.parity.shared::cta.b64 p, [%1], %2;\nselp.u32 %0,1,0,p;\n}"
               : "=r"(ok) : "r"(bar), "r"(parity) : "memory");
  return ok != 0;
}
__device__ __forceinline__ void mbar_wait(uint32_t bar, uint32_t parity) {
  int guard = 0;
  while (!mbar_try(bar, parity)) { if (++guard > (1 << 24)) { g_err = 1; __trap(); } }
}
__device__ __forceinline__ void mbar_wait_cluster(uint32_t bar, uint32_t parity) {
  int guard = 0; uint32_t ok;
  do {
    asm volatile("{\n.reg .pred p;\nmbarrier.try_wait.parity.acquire.cluster.shared::cta.b64 p, [%1], %2;\nselp.u32 %0,1,0,p;\n}"
                 : "=r"(ok) : "r"(bar), "r"(parity) : "memory");
    if (++guard > (1 << 24)) { g_err = 2; __trap(); }
  } while (!ok);
}
__device__ __forceinline__ void tma_load_2d(uint32_t dst, const CUtensorMap* map, int x, int y, uint32_t bar) {
  asm volatile("cp.async.bulk.tensor.2d.shared::cluster.global.mbarrier::complete_tx::bytes [%0], [%1, {%3, %4}], [%2];"
               ::"r"(dst), "l"((uint64_t)map), "r"(bar), "r"(x), "r"(y) : "memory");
}
__device__ __forceinline__ void bulk_g2s(uint32_t dst, const void* src, uint32_t bytes, uint32_t bar) {
  asm volatile("cp.async.bulk.shared::cluster.global.mbarrier::complete_tx::bytes [%0], [%1], %2, [%3];"
               ::"r"(dst), "l"((uint64_t)src), "r"(bytes), "r"(bar) : "memory");
}
__device__ __forceinline__ void bulk_s2g(void* dst, uint32_t src, uint32_t bytes) {
  asm volatile("cp.async.bulk.global.shared::cta.bulk_group [%0], [%1], %2;" ::"l"((uint64_t)dst), "r"(src), "r"(bytes) : "memory");
}
__device__ __forceinline__ void bulk_commit() { asm volatile("cp.async.bulk.commit_group;" ::: "memory"); }
__device__ __forceinline__ void bulk_wait_read0() { asm volatile("cp.async.bulk.wait_group.read 0;" ::: "memory"); }
__device__ __forceinline__ void bulk_wait0() { asm volatile("cp.async.bulk.wait_group 0;" ::: "memory"); }
__device__ __forceinline__ void fence_async_smem() { asm volatile("fence.proxy.async.shared::cta;" ::: "memory"); }
__device__ __forceinline__ void wg_fence() { asm volatile("wgmma.fence.sync.aligned;" ::: "memory"); }
__device__ __forceinline__ void wg_commit() { asm volatile("wgmma.commit_group.sync.aligned;" ::: "memory"); }
template <int N> __device__ __forceinline__ void wg_wait() { asm volatile("wgmma.wait_group.sync.aligned %0;" ::"n"(N) : "memory"); }
__device__ __forceinline__ void bar_sync(int id, int n) { asm volatile("bar.sync %0, %1;" ::"r"(id), "r"(n) : "memory"); }

__device__ __forceinline__ void mma16816(float* c, uint32_t a0, uint32_t a1, uint32_t a2, uint32_t a3, uint32_t b0, uint32_t b1) {
  asm volatile("mma.sync.aligned.m16n8k16.row.col.f32.bf16.bf16.f32 {%0,%1,%2,%3},{%4,%5,%6,%7},{%8,%9},{%0,%1,%2,%3};"
               : "+f"(c[0]), "+f"(c[1]), "+f"(c[2]), "+f"(c[3]) : "r"(a0), "r"(a1), "r"(a2), "r"(a3), "r"(b0), "r"(b1));
}
__device__ __forceinline__ void ldsm4(uint32_t* r, uint32_t addr) {
  asm volatile("ldmatrix.sync.aligned.m8n8.x4.shared.b16 {%0,%1,%2,%3}, [%4];"
               : "=r"(r[0]), "=r"(r[1]), "=r"(r[2]), "=r"(r[3]) : "r"(addr) : "memory");
}
__device__ __forceinline__ void ldsm4t(uint32_t* r, uint32_t addr) {
  asm volatile("ldmatrix.sync.aligned.m8n8.x4.trans.shared.b16 {%0,%1,%2,%3}, [%4];"
               : "=r"(r[0]), "=r"(r[1]), "=r"(r[2]), "=r"(r[3]) : "r"(addr) : "memory");
}
__device__ __forceinline__ void ldsm2(uint32_t* r, uint32_t addr) {
  asm volatile("ldmatrix.sync.aligned.m8n8.x2.shared.b16 {%0,%1}, [%2];" : "=r"(r[0]), "=r"(r[1]) : "r"(addr) : "memory");
}
__device__ __forceinline__ void ldsm2t(uint32_t* r, uint32_t addr) {
  asm volatile("ldmatrix.sync.aligned.m8n8.x2.trans.shared.b16 {%0,%1}, [%2];" : "=r"(r[0]), "=r"(r[1]) : "r"(addr) : "memory");
}
__device__ __forceinline__ void stsm4(uint32_t addr, uint32_t r0, uint32_t r1, uint32_t r2, uint32_t r3) {
  asm volatile("stmatrix.sync.aligned.m8n8.x4.shared.b16 [%0], {%1,%2,%3,%4};" ::"r"(addr), "r"(r0), "r"(r1), "r"(r2), "r"(r3) : "memory");
}
__device__ __forceinline__ uint32_t movtrans(uint32_t a) {
  uint32_t d; asm volatile("movmatrix.sync.aligned.m8n8.trans.b16 %0, %1;" : "=r"(d) : "r"(a)); return d;
}
__device__ __forceinline__ uint4 lds128(uint32_t a) {
  uint4 v; asm volatile("ld.shared.v4.u32 {%0,%1,%2,%3}, [%4];" : "=r"(v.x), "=r"(v.y), "=r"(v.z), "=r"(v.w) : "r"(a) : "memory"); return v;
}
__device__ __forceinline__ float4 lds128f(uint32_t a) {
  float4 v; asm volatile("ld.shared.v4.f32 {%0,%1,%2,%3}, [%4];" : "=f"(v.x), "=f"(v.y), "=f"(v.z), "=f"(v.w) : "r"(a) : "memory"); return v;
}
__device__ __forceinline__ uint2 lds64(uint32_t a) {
  uint2 v; asm volatile("ld.shared.v2.u32 {%0,%1}, [%2];" : "=r"(v.x), "=r"(v.y) : "r"(a) : "memory"); return v;
}
__device__ __forceinline__ void sts128(uint32_t a, uint32_t x, uint32_t y, uint32_t z, uint32_t w) {
  asm volatile("st.shared.v4.u32 [%0], {%1,%2,%3,%4};" ::"r"(a), "r"(x), "r"(y), "r"(z), "r"(w) : "memory");
}
__device__ __forceinline__ void sts128f(uint32_t a, const float* c) {
  asm volatile("st.shared.v4.f32 [%0], {%1,%2,%3,%4};" ::"r"(a), "f"(c[0]), "f"(c[1]), "f"(c[2]), "f"(c[3]) : "memory");
}
__device__ __forceinline__ void sts64(uint32_t a, uint32_t x, uint32_t y) {
  asm volatile("st.shared.v2.u32 [%0], {%1,%2};" ::"r"(a), "r"(x), "r"(y) : "memory");
}
__device__ __forceinline__ uint4 ldg_relaxed128(const void* p) {
  uint4 v; asm volatile("ld.relaxed.gpu.global.v4.u32 {%0,%1,%2,%3}, [%4];" : "=r"(v.x), "=r"(v.y), "=r"(v.z), "=r"(v.w) : "l"(p) : "memory"); return v;
}
__device__ __forceinline__ void stg_relaxed128(void* p, uint32_t x, uint32_t y, uint32_t z, uint32_t w) {
  asm volatile("st.relaxed.gpu.global.v4.u32 [%0], {%1,%2,%3,%4};" ::"l"(p), "r"(x), "r"(y), "r"(z), "r"(w) : "memory");
}
__device__ __forceinline__ void stg_relaxed32(void* p, uint32_t x) {
  asm volatile("st.relaxed.gpu.global.u32 [%0], %1;" ::"l"(p), "r"(x) : "memory");
}
__device__ __forceinline__ uint32_t ld_acquire32(const void* p) {
  uint32_t v; asm volatile("ld.acquire.gpu.global.u32 %0, [%1];" : "=r"(v) : "l"(p) : "memory"); return v;
}
__device__ __forceinline__ void red_release_add(void* p, uint32_t v) {
  asm volatile("red.release.gpu.global.add.u32 [%0], %1;" ::"l"(p), "r"(v) : "memory");
}
__device__ __forceinline__ void fence_async_all() { asm volatile("fence.proxy.async;" ::: "memory"); }
__device__ __forceinline__ uint32_t mapa(uint32_t a, uint32_t rank) {
  uint32_t r; asm volatile("mapa.shared::cluster.u32 %0, %1, %2;" : "=r"(r) : "r"(a), "r"(rank)); return r;
}
__device__ __forceinline__ void st_async128(uint32_t a, uint32_t x, uint32_t y, uint32_t z, uint32_t w, uint32_t bar) {
  asm volatile("st.async.weak.shared::cluster.mbarrier::complete_tx::bytes.v4.u32 [%0], {%1,%2,%3,%4}, [%5];"
               ::"r"(a), "r"(x), "r"(y), "r"(z), "r"(w), "r"(bar) : "memory");
}
__device__ __forceinline__ void st_async64(uint32_t a, uint32_t x, uint32_t y, uint32_t bar) {
  asm volatile("st.async.weak.shared::cluster.mbarrier::complete_tx::bytes.v2.u32 [%0], {%1,%2}, [%3];"
               ::"r"(a), "r"(x), "r"(y), "r"(bar) : "memory");
}
__device__ __forceinline__ void cp_async16(uint32_t dst, const void* src) {
  asm volatile("cp.async.cg.shared.global [%0], [%1], 16;" ::"r"(dst), "l"(src) : "memory");
}
__device__ __forceinline__ void cp_async_wait_all() { asm volatile("cp.async.wait_all;" ::: "memory"); }

__device__ __forceinline__ void wgmma_n128(float* d, uint64_t da, uint64_t db, int scale_d) {
  asm volatile("{\n.reg .pred p;\nsetp.ne.b32 p, %66, 0;\n"
    "wgmma.mma_async.sync.aligned.m64n128k16.f32.bf16.bf16 {%0,%1,%2,%3,%4,%5,%6,%7,%8,%9,%10,%11,%12,%13,%14,%15,%16,%17,%18,%19,%20,%21,%22,%23,%24,%25,%26,%27,%28,%29,%30,%31,%32,%33,%34,%35,%36,%37,%38,%39,%40,%41,%42,%43,%44,%45,%46,%47,%48,%49,%50,%51,%52,%53,%54,%55,%56,%57,%58,%59,%60,%61,%62,%63}, %64, %65, p, 1, 1, 0, 1;\n}\n"
    : "+f"(d[0]),"+f"(d[1]),"+f"(d[2]),"+f"(d[3]),"+f"(d[4]),"+f"(d[5]),"+f"(d[6]),"+f"(d[7]),"+f"(d[8]),"+f"(d[9]),"+f"(d[10]),"+f"(d[11]),"+f"(d[12]),"+f"(d[13]),"+f"(d[14]),"+f"(d[15]),"+f"(d[16]),"+f"(d[17]),"+f"(d[18]),"+f"(d[19]),"+f"(d[20]),"+f"(d[21]),"+f"(d[22]),"+f"(d[23]),"+f"(d[24]),"+f"(d[25]),"+f"(d[26]),"+f"(d[27]),"+f"(d[28]),"+f"(d[29]),"+f"(d[30]),"+f"(d[31]),"+f"(d[32]),"+f"(d[33]),"+f"(d[34]),"+f"(d[35]),"+f"(d[36]),"+f"(d[37]),"+f"(d[38]),"+f"(d[39]),"+f"(d[40]),"+f"(d[41]),"+f"(d[42]),"+f"(d[43]),"+f"(d[44]),"+f"(d[45]),"+f"(d[46]),"+f"(d[47]),"+f"(d[48]),"+f"(d[49]),"+f"(d[50]),"+f"(d[51]),"+f"(d[52]),"+f"(d[53]),"+f"(d[54]),"+f"(d[55]),"+f"(d[56]),"+f"(d[57]),"+f"(d[58]),"+f"(d[59]),"+f"(d[60]),"+f"(d[61]),"+f"(d[62]),"+f"(d[63])
    : "l"(da), "l"(db), "r"(scale_d));
}

__device__ __forceinline__ void wgmma_n256(float* d, uint64_t da, uint64_t db, int scale_d) {
  asm volatile("{\n.reg .pred p;\nsetp.ne.b32 p, %130, 0;\n"
    "wgmma.mma_async.sync.aligned.m64n256k16.f32.bf16.bf16 {%0,%1,%2,%3,%4,%5,%6,%7,%8,%9,%10,%11,%12,%13,%14,%15,%16,%17,%18,%19,%20,%21,%22,%23,%24,%25,%26,%27,%28,%29,%30,%31,%32,%33,%34,%35,%36,%37,%38,%39,%40,%41,%42,%43,%44,%45,%46,%47,%48,%49,%50,%51,%52,%53,%54,%55,%56,%57,%58,%59,%60,%61,%62,%63,%64,%65,%66,%67,%68,%69,%70,%71,%72,%73,%74,%75,%76,%77,%78,%79,%80,%81,%82,%83,%84,%85,%86,%87,%88,%89,%90,%91,%92,%93,%94,%95,%96,%97,%98,%99,%100,%101,%102,%103,%104,%105,%106,%107,%108,%109,%110,%111,%112,%113,%114,%115,%116,%117,%118,%119,%120,%121,%122,%123,%124,%125,%126,%127}, %128, %129, p, 1, 1, 0, 1;\n}\n"
    : "+f"(d[0]),"+f"(d[1]),"+f"(d[2]),"+f"(d[3]),"+f"(d[4]),"+f"(d[5]),"+f"(d[6]),"+f"(d[7]),"+f"(d[8]),"+f"(d[9]),"+f"(d[10]),"+f"(d[11]),"+f"(d[12]),"+f"(d[13]),"+f"(d[14]),"+f"(d[15]),"+f"(d[16]),"+f"(d[17]),"+f"(d[18]),"+f"(d[19]),"+f"(d[20]),"+f"(d[21]),"+f"(d[22]),"+f"(d[23]),"+f"(d[24]),"+f"(d[25]),"+f"(d[26]),"+f"(d[27]),"+f"(d[28]),"+f"(d[29]),"+f"(d[30]),"+f"(d[31]),"+f"(d[32]),"+f"(d[33]),"+f"(d[34]),"+f"(d[35]),"+f"(d[36]),"+f"(d[37]),"+f"(d[38]),"+f"(d[39]),"+f"(d[40]),"+f"(d[41]),"+f"(d[42]),"+f"(d[43]),"+f"(d[44]),"+f"(d[45]),"+f"(d[46]),"+f"(d[47]),"+f"(d[48]),"+f"(d[49]),"+f"(d[50]),"+f"(d[51]),"+f"(d[52]),"+f"(d[53]),"+f"(d[54]),"+f"(d[55]),"+f"(d[56]),"+f"(d[57]),"+f"(d[58]),"+f"(d[59]),"+f"(d[60]),"+f"(d[61]),"+f"(d[62]),"+f"(d[63]),"+f"(d[64]),"+f"(d[65]),"+f"(d[66]),"+f"(d[67]),"+f"(d[68]),"+f"(d[69]),"+f"(d[70]),"+f"(d[71]),"+f"(d[72]),"+f"(d[73]),"+f"(d[74]),"+f"(d[75]),"+f"(d[76]),"+f"(d[77]),"+f"(d[78]),"+f"(d[79]),"+f"(d[80]),"+f"(d[81]),"+f"(d[82]),"+f"(d[83]),"+f"(d[84]),"+f"(d[85]),"+f"(d[86]),"+f"(d[87]),"+f"(d[88]),"+f"(d[89]),"+f"(d[90]),"+f"(d[91]),"+f"(d[92]),"+f"(d[93]),"+f"(d[94]),"+f"(d[95]),"+f"(d[96]),"+f"(d[97]),"+f"(d[98]),"+f"(d[99]),"+f"(d[100]),"+f"(d[101]),"+f"(d[102]),"+f"(d[103]),"+f"(d[104]),"+f"(d[105]),"+f"(d[106]),"+f"(d[107]),"+f"(d[108]),"+f"(d[109]),"+f"(d[110]),"+f"(d[111]),"+f"(d[112]),"+f"(d[113]),"+f"(d[114]),"+f"(d[115]),"+f"(d[116]),"+f"(d[117]),"+f"(d[118]),"+f"(d[119]),"+f"(d[120]),"+f"(d[121]),"+f"(d[122]),"+f"(d[123]),"+f"(d[124]),"+f"(d[125]),"+f"(d[126]),"+f"(d[127])
    : "l"(da), "l"(db), "r"(scale_d));
}

__global__ void __launch_bounds__(256) mod_kernel(const bf16* __restrict__ c, const bf16* __restrict__ w_mod,
                                                  const bf16* __restrict__ mem0) {
  __shared__ float s_c[DM];
  __shared__ float s_red[64][33];
  const int tid = threadIdx.x;
  for (int i = tid; i < DM; i += 256) {
    float v = __bfloat162float(c[i]);
    s_c[i] = bfr(v / (1.f + __expf(-v)));
  }
  __syncthreads();
  {
    const int cg = tid & 3, kg = tid >> 2;
    const int col0 = blockIdx.x * 32 + cg * 8;
    float acc[8];
#pragma unroll
    for (int j = 0; j < 8; j++) acc[j] = 0.f;
    uint4 w[10];
#pragma unroll
    for (int i = 0; i < 10; i++) w[i] = *reinterpret_cast<const uint4*>(w_mod + (size_t)(kg * 10 + i) * (6 * DM) + col0);
#pragma unroll
    for (int i = 0; i < 10; i++) {
      float cv = s_c[kg * 10 + i];
      acc[0] += cv * lo2f(w[i].x); acc[1] += cv * hi2f(w[i].x);
      acc[2] += cv * lo2f(w[i].y); acc[3] += cv * hi2f(w[i].y);
      acc[4] += cv * lo2f(w[i].z); acc[5] += cv * hi2f(w[i].z);
      acc[6] += cv * lo2f(w[i].w); acc[7] += cv * hi2f(w[i].w);
    }
#pragma unroll
    for (int j = 0; j < 8; j++) s_red[kg][cg * 8 + j] = acc[j];
  }
  __syncthreads();
  if (tid < 32) {
    float s = 0.f;
    for (int i = 0; i < 64; i++) s += s_red[i][tid];
    g_mod[blockIdx.x * 32 + tid] = bfr(s);
  }
  const int gt = blockIdx.x * 256 + tid, GT = gridDim.x * 256;
  uint4* pp = reinterpret_cast<uint4*>(g_part);
  for (int i = gt; i < 2 * 40 * 8 * 32 * 16 / 4; i += GT) pp[i] = make_uint4(0, 0, 0, 0);
  if (gt < 16 * 48) g_kvflag[gt] = 0;
  if (gt == 0) g_resident = 0;
  uint4* pm = reinterpret_cast<uint4*>(g_memb);
  for (int i = gt + 640; i < 4 * 640; i += GT) pm[i] = make_uint4(~0u, ~0u, ~0u, ~0u);
  if (gt < 2560) {
    int i = gt & 3, lane = (gt >> 2) & 31, kk = gt >> 7;
    int n = lane >> 2, u = 4 * kk + (lane & 3), col = 16 * (u >> 1) + 4 * (u & 1) + i;
    uint32_t lo = reinterpret_cast<const unsigned short*>(mem0)[n * DM + col];
    uint32_t hi = reinterpret_cast<const unsigned short*>(mem0)[n * DM + col + 8];
    uint32_t wv = lo | (hi << 16);
    if (wv == 0xffffffffu) wv = 0x7fff7fffu;
    g_memb[gt] = wv;
  }
}

__global__ void __launch_bounds__(256) ln_kernel(const bf16* __restrict__ x, bf16* __restrict__ out, int shift_off, int scale_off, unsigned gate) {
  const int warp = threadIdx.x >> 5, lane = threadIdx.x & 31;
  const int row = blockIdx.x * 8 + warp;
  const uint2* xr = reinterpret_cast<const uint2*>(x + (size_t)row * DM);
  float v[20];
#pragma unroll
  for (int i = 0; i < 5; i++) {
    uint2 u = xr[i * 32 + lane];
    v[i * 4 + 0] = lo2f(u.x); v[i * 4 + 1] = hi2f(u.x); v[i * 4 + 2] = lo2f(u.y); v[i * 4 + 3] = hi2f(u.y);
  }
  float s = 0.f;
#pragma unroll
  for (int i = 0; i < 20; i++) s += v[i];
#pragma unroll
  for (int o = 16; o; o >>= 1) s += __shfl_xor_sync(~0u, s, o);
  const float mean = s * (1.f / DM);
  float q = 0.f;
#pragma unroll
  for (int i = 0; i < 20; i++) { float d = v[i] - mean; q += d * d; }
#pragma unroll
  for (int o = 16; o; o >>= 1) q += __shfl_xor_sync(~0u, q, o);
  const float mb = bfr(mean);
  const float den = bfr(sqrtf(bfr(bfr(q * (1.f / DM)) + 1e-5f)));
  uint2* orow = reinterpret_cast<uint2*>(out + (size_t)row * DM);
#pragma unroll
  for (int i = 0; i < 5; i++) {
    const int col = (i * 32 + lane) * 4;
    float4 sh = *reinterpret_cast<const float4*>(g_mod + shift_off + col);
    float4 sc = *reinterpret_cast<const float4*>(g_mod + scale_off + col);
    float r0 = bfr(bfr(bfr(v[i * 4 + 0] - mb) / den) * bfr(1.f + sc.x)) + sh.x;
    float r1 = bfr(bfr(bfr(v[i * 4 + 1] - mb) / den) * bfr(1.f + sc.y)) + sh.y;
    float r2 = bfr(bfr(bfr(v[i * 4 + 2] - mb) / den) * bfr(1.f + sc.z)) + sh.z;
    float r3 = bfr(bfr(bfr(v[i * 4 + 3] - mb) / den) * bfr(1.f + sc.w)) + sh.w;
    orow[i * 32 + lane] = make_uint2(pack2(r0, r1), pack2(r2, r3));
  }
  if (gate && blockIdx.x == 0 && threadIdx.x == 0) {
    for (int i = 0; i < 20000 && ld_acquire32(&g_resident) < gate; i++) __nanosleep(50);
  }
}

enum { EPI_QKV = 0, EPI_RES = 1, EPI_GEGLU = 2 };
struct GemmP {
  int m_tiles, n_tiles, kblocks;
  int n_off;
  const bf16* res;
  bf16* out;
  int gate_off;
  int m_major;
  int use_flags;
};
template <int BN> struct GemmCfg {
  static constexpr int STAGES = (BN == 256) ? 4 : 5;
  static constexpr int A_BYTES = 128 * 64 * 2, B_BYTES = BN * 64 * 2, STAGE = A_BYTES + B_BYTES;
  static constexpr int STG_OFF = STAGES * STAGE;
  static constexpr int BAR_OFF = STG_OFF + 8 * 4096;
  static constexpr int SMEM = BAR_OFF + 128 + 1024;
};
__device__ __forceinline__ float gelu_tanh(float x) {
  float u = 0.7978845608028654f * (x + 0.044715f * x * x * x);
  float t = 1.f - 2.f / (1.f + __expf(2.f * u));
  return 0.5f * x * (1.f + t);
}

template <int BN, int EPI>
__global__ void __launch_bounds__(288, 1)
gemm_kernel(const __grid_constant__ CUtensorMap tmA, const __grid_constant__ CUtensorMap tmB0,
            const __grid_constant__ CUtensorMap tmB1, const __grid_constant__ CUtensorMap tmB2, GemmP p) {
  using C = GemmCfg<BN>;
  extern __shared__ uint8_t smem_raw[];
  const uint32_t sb = (smem_u32(smem_raw) + 1023u) & ~1023u;
  const uint32_t full0 = sb + C::BAR_OFF, empty0 = full0 + 8 * C::STAGES;
  const int warp = threadIdx.x >> 5, lane = threadIdx.x & 31;
  if (threadIdx.x == 0) {
    for (int i = 0; i < C::STAGES; i++) { mbar_init(full0 + 8 * i, 1); mbar_init(empty0 + 8 * i, 8); }
    asm volatile("fence.mbarrier_init.release.cluster;" ::: "memory");
  }
  __syncthreads();
  const int ntiles = p.m_tiles * p.n_tiles;
  if (warp == 8) {
    if (lane == 0) {
      int st = 0; uint32_t ph = 1;
      for (int t = blockIdx.x; t < ntiles; t += gridDim.x) {
        const int mt = p.m_major ? t / p.n_tiles : t % p.m_tiles, nt = p.m_major ? t % p.n_tiles : t / p.m_tiles;
        for (int kb = 0; kb < p.kblocks; kb++) {
          mbar_wait(empty0 + 8 * st, ph);
          const uint32_t fb = full0 + 8 * st, sa = sb + st * C::STAGE, sbb = sa + C::A_BYTES;
          mbar_expect_tx(fb, C::STAGE);
          tma_load_2d(sa, &tmA, kb * 64, mt * 128, fb);
          if (EPI == EPI_QKV) {
            const int gn = (nt + p.n_off) * BN, mat = gn / HD, col = gn % HD;
            const CUtensorMap* mp = mat == 0 ? &tmB0 : (mat == 1 ? &tmB1 : &tmB2);
#pragma unroll
            for (int b = 0; b < BN / 64; b++) tma_load_2d(sbb + b * 8192, mp, col + b * 64, kb * 64, fb);
          } else if (EPI == EPI_GEGLU) {
#pragma unroll
            for (int b = 0; b < BN / 128; b++) {
              tma_load_2d(sbb + (2 * b) * 8192, &tmB0, nt * (BN / 2) + b * 64, kb * 64, fb);
              tma_load_2d(sbb + (2 * b + 1) * 8192, &tmB1, nt * (BN / 2) + b * 64, kb * 64, fb);
            }
          } else {
#pragma unroll
            for (int b = 0; b < BN / 64; b++) tma_load_2d(sbb + b * 8192, &tmB0, nt * BN + b * 64, kb * 64, fb);
          }
          if (++st == C::STAGES) { st = 0; ph ^= 1; }
        }
      }
    }
    return;
  }
  const int wg = warp >> 2;
  float acc[BN / 2];
  int st = 0; uint32_t ph = 0;
  const uint32_t stg = sb + C::STG_OFF + warp * 4096;
  for (int t = blockIdx.x; t < ntiles; t += gridDim.x) {
    const int mt = p.m_major ? t / p.n_tiles : t % p.m_tiles, nt = p.m_major ? t % p.n_tiles : t / p.m_tiles;
    int prev = -1;
    for (int kb = 0; kb < p.kblocks; kb++) {
      mbar_wait(full0 + 8 * st, ph);
      const uint32_t sa = sb + st * C::STAGE + wg * 8192, sbb = sb + st * C::STAGE + C::A_BYTES;
      const uint64_t da = (uint64_t)((sa & 0x3FFFF) >> 4) | ((uint64_t)1 << 16) | ((uint64_t)(1024 >> 4) << 32) | ((uint64_t)1 << 62);
      const uint64_t db = (uint64_t)((sbb & 0x3FFFF) >> 4) | ((uint64_t)(8192 >> 4) << 16) | ((uint64_t)(1024 >> 4) << 32) | ((uint64_t)1 << 62);
      wg_fence();
#pragma unroll
      for (int k = 0; k < 4; k++) {
        if (BN == 256) wgmma_n256(acc, da + (uint64_t)(k * 2), db + (uint64_t)(k * 128), (kb | k) != 0);
        else wgmma_n128(acc, da + (uint64_t)(k * 2), db + (uint64_t)(k * 128), (kb | k) != 0);
      }
      wg_commit();
      if (prev >= 0) { wg_wait<1>(); if (lane == 0) mbar_arrive(empty0 + 8 * prev); }
      prev = st;
      if (++st == C::STAGES) { st = 0; ph ^= 1; }
    }
    wg_wait<0>();
    if (lane == 0) mbar_arrive(empty0 + 8 * prev);
    const int row0 = mt * 128 + warp * 16;
    const int srow = ((lane >> 3) & 1) * 8 + (lane & 7);
    const int schunk = lane >> 4;
    if (EPI == EPI_QKV) {
      const int gn = (nt + p.n_off) * BN, mat = gn / HD, head0 = (gn % HD) / DH;
      bf16* dstb = mat == 0 ? g_q : (mat == 1 ? g_k : g_v);
#pragma unroll
      for (int hh = 0; hh < BN / 128; hh++) {
        if (lane == 0) bulk_wait_read0();
        __syncwarp();
#pragma unroll
        for (int j = 0; j < 16; j += 2) {
          const float* a = acc + hh * 64 + j * 4;
          stsm4(stg + srow * 256 + (((j + schunk) ^ (srow & 7)) << 4), pack2(a[0], a[1]), pack2(a[2], a[3]), pack2(a[4], a[5]), pack2(a[6], a[7]));
        }
        fence_async_smem();
        __syncwarp();
        if (lane == 0) { bulk_s2g(dstb + ((size_t)(head0 + hh) * S_TOK + row0) * DH, stg, 4096); bulk_commit(); }
      }
      if (p.use_flags && lane == 0) {
        bulk_wait0();
        fence_async_all();
        red_release_add(&g_kvflag[mt * 48 + nt + p.n_off], 1u);
      }
    } else if (EPI == EPI_RES) {
#pragma unroll
      for (int hh = 0; hh < BN / 128; hh++) {
        __syncwarp();
#pragma unroll
        for (int j = 0; j < 16; j += 2) {
          const float* a = acc + hh * 64 + j * 4;
          stsm4(stg + srow * 256 + (((j + schunk) ^ (srow & 7)) << 4), pack2(a[0], a[1]), pack2(a[2], a[3]), pack2(a[4], a[5]), pack2(a[6], a[7]));
        }
        __syncwarp();
        const int ch = lane & 15, col = nt * BN + hh * 128 + ch * 8;
        const float4 g0 = *reinterpret_cast<const float4*>(g_mod + p.gate_off + col);
        const float4 g1 = *reinterpret_cast<const float4*>(g_mod + p.gate_off + col + 4);
#pragma unroll
        for (int i = 0; i < 8; i++) {
          const int r = i * 2 + (lane >> 4);
          uint4 a = lds128(stg + r * 256 + ((ch ^ (r & 7)) << 4));
          uint4 x = *reinterpret_cast<const uint4*>(p.res + (size_t)(row0 + r) * DM + col);
          uint4 o;
          o.x = pack2(lo2f(x.x) + bfr(g0.x * lo2f(a.x)), hi2f(x.x) + bfr(g0.y * hi2f(a.x)));
          o.y = pack2(lo2f(x.y) + bfr(g0.z * lo2f(a.y)), hi2f(x.y) + bfr(g0.w * hi2f(a.y)));
          o.z = pack2(lo2f(x.z) + bfr(g1.x * lo2f(a.z)), hi2f(x.z) + bfr(g1.y * hi2f(a.z)));
          o.w = pack2(lo2f(x.w) + bfr(g1.z * lo2f(a.w)), hi2f(x.w) + bfr(g1.w * hi2f(a.w)));
          *reinterpret_cast<uint4*>(p.out + (size_t)(row0 + r) * DM + col) = o;
        }
      }
    } else {
#pragma unroll
      for (int hh = 0; hh < BN / 128; hh++) {
        __syncwarp();
#pragma unroll
        for (int j = 0; j < 8; j += 2) {
          const float* g = acc + hh * 64 + j * 4;
          const float* u = g + 32;
          float r[8];
#pragma unroll
          for (int e = 0; e < 8; e++) r[e] = bfr(gelu_tanh(bfr(g[e]))) * bfr(u[e]);
          stsm4(stg + srow * 128 + (((j + schunk) ^ (srow & 7)) << 4), pack2(r[0], r[1]), pack2(r[2], r[3]), pack2(r[4], r[5]), pack2(r[6], r[7]));
        }
        __syncwarp();
        const int ch = lane & 7, col = nt * (BN / 2) + hh * 64 + ch * 8;
#pragma unroll
        for (int i = 0; i < 4; i++) {
          const int r = i * 4 + (lane >> 3);
          uint4 a = lds128(stg + r * 128 + ((ch ^ (r & 7)) << 4));
          *reinterpret_cast<uint4*>(g_act + (size_t)(row0 + r) * FF + col) = a;
        }
      }
    }
  }
  if (EPI == EPI_QKV && lane == 0) bulk_wait0();
}

#define PROF(i)
#define DELAY_A 700
#define DELAY_B 2000
namespace rc {
constexpr int OFF_VW = 0;
constexpr int OFF_WO = OFF_VW + 40960;
constexpr int OFF_K = OFF_WO + 24576;
constexpr int OFF_V = OFF_K + 16384;
constexpr int OFF_RED = OFF_V + 16384;
constexpr int OFF_B = OFF_RED + 16384;
constexpr int OFF_S = OFF_B + 10240;
constexpr int OFF_VM = OFF_S + 3840;
constexpr int OFF_F = OFF_VM + 2048;
constexpr int OFF_O = OFF_F + 2048;
constexpr int OFF_BAR = OFF_O + 2048;
constexpr int OFF_STG = OFF_BAR + 128;
constexpr int SMEM = OFF_STG + 61440 + 1024;
constexpr int NCTA = 96;
}
__device__ __forceinline__ float ex2(float x) { float y; asm("ex2.approx.ftz.f32 %0, %1;" : "=f"(y) : "f"(x)); return y; }
__device__ __forceinline__ void bar_arrive(int id, int n) { asm volatile("bar.arrive %0, %1;" ::"r"(id), "r"(n) : "memory"); }

__global__ void __cluster_dims__(3, 1, 1) __launch_bounds__(384, 1)
rec_kernel(const bf16* __restrict__ Wq, const bf16* __restrict__ Wk, const bf16* __restrict__ Wv, const bf16* __restrict__ Wo) {
  using namespace rc;
  extern __shared__ uint8_t smem_raw[];
  const uint32_t sb = (smem_u32(smem_raw) + 1023u) & ~1023u;
  const int tid = threadIdx.x, warp = tid >> 5, lane = tid & 31;
  const int head = blockIdx.x / 3, rank = blockIdx.x % 3;
  const int rho = lane >> 2, jj = lane & 3;
  const int kap = (lane >> 4) * 8 + (lane & 7);
  const int dhalf = (lane >> 3) & 1;
  const uint32_t bar_kv = sb + OFF_BAR, bar_xs = bar_kv + 16, bar_xv = bar_kv + 24;
  const int wt0 = rank * 13, wnt = rank == 2 ? 14 : 13;
  const int nqk = rank == 2 ? 2 : 3;
  if (tid == 0) {
    atomicAdd(&g_resident, 1u);
    mbar_init(bar_kv, 1); mbar_init(bar_kv + 8, 1); mbar_init(bar_xs, 1); mbar_init(bar_xv, 1);
    asm volatile("fence.mbarrier_init.release.cluster;" ::: "memory");
  }
  asm volatile("barrier.cluster.arrive.aligned;\nbarrier.cluster.wait.aligned;" ::: "memory");

  if (warp < 8) {
    asm volatile("setmaxnreg.inc.sync.aligned.u32 200;");
    const int mg = warp >> 2, kq = warp & 3;
    auto tile_src = [&](int i) -> const bf16* {
      if (rank < 2) {
        if (i < 3) return Wq + head * DH + 48 * rank + 16 * i;
        if (i < 6) return Wk + head * DH + 48 * rank + 16 * (i - 3);
        return Wv + head * DH + 16 * (2 * rank + (i - 6));
      } else {
        if (i < 2) return Wq + head * DH + 96 + 16 * i;
        if (i == 2) return Wv + head * DH + 64;
        if (i < 5) return Wk + head * DH + 96 + 16 * (i - 3);
        if (i == 5) return Wv + head * DH + 80;
        return Wv + head * DH + 96 + 16 * (i - 6);
      }
    };
    const int kcol0 = 16 * ((kap & 7) >> 2) + 4 * (((kap & 7) >> 1) & 1) + (kap >> 3) + 8 * (kap & 1);
    uint32_t wa[3][10][4];
    uint32_t wo[8][4];
    const uint32_t lrow = sb + OFF_STG + (kq * 160 + kcol0) * 32 + dhalf * 16;
#pragma unroll
    for (int pass = 0; pass < 3; pass++) {
      const int nt = pass < 2 ? 3 : 2;
      for (int ti = 0; ti < nt; ti++) {
        const bf16* src = tile_src(pass * 3 + ti);
        for (int e = tid; e < 1280; e += 256) {
          const int r = e >> 1, hf = e & 1;
          cp_async16(sb + OFF_STG + ti * 20480 + r * 32 + hf * 16, src + (size_t)r * HD + hf * 8);
        }
      }
      cp_async_wait_all();
      bar_sync(9, 256);
      if (pass < 2) {
        if (mg == pass) {
#pragma unroll
          for (int ti = 0; ti < 3; ti++)
#pragma unroll
            for (int ks = 0; ks < 10; ks++) ldsm4t(wa[ti][ks], lrow + ti * 20480 + ((ks >> 1) * 32 + (ks & 1) * 2) * 32);
        }
      } else {
#pragma unroll
        for (int ks = 0; ks < 10; ks++) {
          uint32_t r[4];
          ldsm4t(r, lrow + mg * 20480 + ((ks >> 1) * 32 + (ks & 1) * 2) * 32);
          sts128(sb + OFF_VW + (mg * 40 + kq * 10 + ks) * 512 + lane * 16, r[0], r[1], r[2], r[3]);
        }
      }
      bar_sync(9, 256);
    }
    {
      const int cpr = wnt * 2;
      for (int e = tid; e < 128 * cpr; e += 256) {
        const int r = e / cpr, c = e % cpr;
        cp_async16(sb + OFF_STG + r * 464 + c * 16, Wo + (size_t)(head * DH + r) * DM + wt0 * 16 + c * 8);
      }
      cp_async_wait_all();
      bar_sync(9, 256);
#pragma unroll
      for (int ks = 0; ks < 8; ks++) ldsm4t(wo[ks], sb + OFF_STG + (ks * 16 + kap) * 464 + warp * 32 + dhalf * 16);
      for (int t = 8; t < wnt; t++) {
        uint32_t r[4];
        ldsm4t(r, sb + OFF_STG + (warp * 16 + kap) * 464 + t * 32 + dhalf * 16);
        sts128(sb + OFF_WO + ((t - 8) * 8 + warp) * 512 + lane * 16, r[0], r[1], r[2], r[3]);
      }
    }
    bar_sync(10, 384);
    uint32_t t_pub = (uint32_t)clock() - DELAY_B;
    const uint32_t vb = sb + OFF_VW + (mg * 40 + kq * 10) * 512 + lane * 16;
    const int ttype = rank < 2 ? (warp < 3 ? 0 : (warp < 6 ? 1 : 2)) : ((warp == 2 || warp >= 5) ? 2 : (warp < 2 ? 0 : 1));
    const int vt = rank < 2 ? 2 * rank + (warp - 6) : (warp == 2 ? 4 : (warp == 5 ? 5 : warp));

    for (int s = 0; s < NSEG; s++) {
      const uint32_t par = s & 1;
      const bool last = s == NSEG - 1;
      PROF(0);
      const uint4 va0 = lds128(vb);
      {
        const uint4* src = reinterpret_cast<const uint4*>(g_memb) + (s & 3) * 640 + (kq * 5 + mg * 3) * 32 + lane;
        while ((int)((uint32_t)clock() - t_pub) < DELAY_B) { }
        uint4 x0, x1, x2 = make_uint4(0, 0, 0, 0);
        int guard = 0;
        while (true) {
          x0 = ldg_relaxed128(src); x1 = ldg_relaxed128(src + 32);
          if (mg == 0) x2 = ldg_relaxed128(src + 64);
          const bool ok = x0.x != ~0u && x0.y != ~0u && x0.z != ~0u && x0.w != ~0u && x1.x != ~0u && x1.y != ~0u && x1.z != ~0u && x1.w != ~0u &&
                          x2.x != ~0u && x2.y != ~0u && x2.z != ~0u && x2.w != ~0u;
          if (__all_sync(~0u, ok)) break;
          if (++guard > (1 << 22)) { g_err = 3; __trap(); }
        }
        const uint32_t bb = sb + OFF_B + (kq * 5 + mg * 3) * 512 + lane * 16;
        sts128(bb, x0.x, x0.y, x0.z, x0.w); sts128(bb + 512, x1.x, x1.y, x1.z, x1.w);
        if (mg == 0) sts128(bb + 1024, x2.x, x2.y, x2.z, x2.w);
        bar_sync(1 + kq, 64);
      }
      PROF(1);
      {
        float c[4][4];
#pragma unroll
        for (int ti = 0; ti < 4; ti++) c[ti][0] = c[ti][1] = c[ti][2] = c[ti][3] = 0.f;
        const uint32_t bb = sb + OFF_B + kq * 2560 + lane * 16;
        uint4 bf[5];
#pragma unroll
        for (int kk = 0; kk < 5; kk++) bf[kk] = lds128(bb + kk * 512);
        uint4 an = va0;
#pragma unroll
        for (int ks = 0; ks < 10; ks++) {
          const uint32_t b0 = (ks & 1) ? bf[ks >> 1].z : bf[ks >> 1].x, b1 = (ks & 1) ? bf[ks >> 1].w : bf[ks >> 1].y;
          const uint4 a0 = an;
          if (ks < 9) an = lds128(vb + (ks + 1) * 512);
#pragma unroll
          for (int ti = 0; ti < 3; ti++) mma16816(c[ti], wa[ti][ks][0], wa[ti][ks][1], wa[ti][ks][2], wa[ti][ks][3], b0, b1);
          mma16816(c[3], a0.x, a0.y, a0.z, a0.w, b0, b1);
        }
#pragma unroll
        for (int ti = 0; ti < 3; ti++) sts128f(sb + OFF_RED + ((mg * 3 + ti) * 4 + kq) * 512 + lane * 16, c[ti]);
        sts128f(sb + OFF_RED + ((6 + mg) * 4 + kq) * 512 + lane * 16, c[3]);
      }
      PROF(2);
      bar_sync(5, 256);
      {
        const uint32_t ra = sb + OFF_RED + warp * 2048 + lane * 16;
        float4 q0 = lds128f(ra), q1 = lds128f(ra + 512), q2 = lds128f(ra + 1024), q3 = lds128f(ra + 1536);
        const uint32_t a0 = pack2((q0.x + q1.x) + (q2.x + q3.x), (q0.y + q1.y) + (q2.y + q3.y));
        const uint32_t a1 = pack2((q0.z + q1.z) + (q2.z + q3.z), (q0.w + q1.w) + (q2.w + q3.w));
        if (ttype == 2 && !last) {
#pragma unroll
          for (int r = 0; r < 3; r++) st_async64(mapa(sb + OFF_VM + vt * 256 + lane * 8, r), a0, a1, mapa(bar_xv, r));
        }
        const uint32_t f0 = movtrans(a0), f1 = movtrans(a1);
        if (ttype < 2) sts64(sb + OFF_F + warp * 256 + lane * 8, f0, f1);
        bar_arrive(6, 384);
        PROF(3);
        if (ttype) {
          const int c0 = ttype == 1 ? rank * 6 + 2 * (warp - 3) : 2 * vt;
          uint32_t* dst = reinterpret_cast<uint32_t*>((ttype == 1 ? g_km : g_vm) + ((size_t)(s * NH + head) * NMEM + rho) * DH);
          dst[((c0 ^ rho) << 2) + jj] = f0;
          dst[(((c0 + 1) ^ rho) << 2) + jj] = f1;
        }
      }
      if (last) break;
      PROF(8);
      bar_sync(8, 384);
      const uint32_t flag = ((s >> 1) & 1) ^ 1;
      {
        float c0[4] = {0.f, 0.f, 0.f, 0.f}, c1[4] = {0.f, 0.f, 0.f, 0.f};
        uint4 ob[4];
#pragma unroll
        for (int i = 0; i < 4; i++) ob[i] = lds128(sb + OFF_O + i * 512 + lane * 16);
#pragma unroll
        for (int i = 0; i < 4; i++) {
          mma16816(c0, wo[2 * i][0], wo[2 * i][1], wo[2 * i][2], wo[2 * i][3], ob[i].x, ob[i].y);
          mma16816(c1, wo[2 * i + 1][0], wo[2 * i + 1][1], wo[2 * i + 1][2], wo[2 * i + 1][3], ob[i].z, ob[i].w);
        }
        float* dst0 = g_part + ((((size_t)par * 160 + (wt0 + warp) * 4 + jj) * 32 + head) * 8 + rho) * 4;
        uint32_t w[4];
#pragma unroll
        for (int e = 0; e < 4; e++) w[e] = (__float_as_uint(c0[e] + c1[e]) & ~1u) | flag;
        stg_relaxed128(dst0, w[0], w[1], w[2], w[3]);
      }
      t_pub = (uint32_t)clock();
      PROF(9);
    }
  } else {
    asm volatile("setmaxnreg.dec.sync.aligned.u32 104;");
    const int aw = warp - 8;
    const bf16* kbase = g_k + (size_t)head * S_TOK * DH;
    const bf16* vbase = g_v + (size_t)head * S_TOK * DH;
    auto load_kv = [&](int sg) {
      if ((sg & 3) == 0) {
        const unsigned* f = g_kvflag + (sg >> 2) * 48 + 16 + (head >> 1);
        int guard = 0;
        while (ld_acquire32(f) < 8u || ld_acquire32(f + 16) < 8u) { __nanosleep(100); if (++guard > (1 << 22)) { g_err = 5; __trap(); } }
        fence_async_all();
      }
      const int b = sg & 1;
      mbar_expect_tx(bar_kv + 8 * b, 16384);
      bulk_g2s(sb + OFF_K + b * 8192, kbase + (size_t)sg * SEG * DH, 8192, bar_kv + 8 * b);
      bulk_g2s(sb + OFF_V + b * 8192, vbase + (size_t)sg * SEG * DH, 8192, bar_kv + 8 * b);
    };
    if (aw == 1 && lane == 0) { load_kv(0); load_kv(1); }
    bar_sync(10, 384);
    uint4 wf[8];
    {
      const uint32_t wb = sb + OFF_WO + aw * 4096 + lane * 16;
#pragma unroll
      for (int i = 0; i < 8; i++) wf[i] = lds128(wb + i * 512);
    }
    const bool two = aw < wnt - 12;
    const int unit = (3 - aw) * NCTA + blockIdx.x;
    const bool is_red = unit < 160;
    for (int s = 0; s < NSEG - 1; s++) {
      const uint32_t par = s & 1;
      if (aw == 0 && lane == 0) { mbar_expect_tx(bar_xs, 3840); mbar_expect_tx(bar_xv, 2048); }
      PROF(0);
      uint32_t kf[3][2], va[2][2][4];
      mbar_wait(bar_kv + 8 * par, (s >> 1) & 1);
      {
        const int key = aw * 8 + (lane & 7);
#pragma unroll
        for (int i = 0; i < 3; i++) {
          const int ch = rank * 6 + 2 * i + dhalf;
          if (i < nqk) ldsm2(kf[i], sb + OFF_K + par * 8192 + key * 256 + ((ch ^ (key & 7)) << 4));
          else kf[i][0] = kf[i][1] = 0u;
        }
#pragma unroll
        for (int m = 0; m < 2; m++)
#pragma unroll
          for (int ks = 0; ks < 2; ks++) {
            const int k2 = ks * 16 + kap, ch = 2 * (aw + 4 * m) + dhalf;
            ldsm4t(va[m][ks], sb + OFF_V + par * 8192 + k2 * 256 + ((ch ^ (k2 & 7)) << 4));
          }
      }
      PROF(1);
      bar_sync(6, 384);
      {
        float sc[2][4], sm[2][4];
        uint2 qa[3], kk[3];
#pragma unroll
        for (int i = 0; i < 3; i++) {
          qa[i] = make_uint2(0u, 0u); kk[i] = make_uint2(0u, 0u);
          if (i < nqk) qa[i] = lds64(sb + OFF_F + i * 256 + lane * 8);
        }
        if (aw == 3) {
#pragma unroll
          for (int i = 0; i < 3; i++) if (i < nqk) kk[i] = lds64(sb + OFF_F + (3 + i) * 256 + lane * 8);
        }
#pragma unroll
        for (int i = 0; i < 2; i++) { sc[i][0] = sc[i][1] = sc[i][2] = sc[i][3] = 0.f; sm[i][0] = sm[i][1] = sm[i][2] = sm[i][3] = 0.f; }
#pragma unroll
        for (int i = 0; i < 3; i++) mma16816(sc[i & 1], qa[i].x, 0u, qa[i].y, 0u, kf[i][0], kf[i][1]);
        if (aw == 3) {
#pragma unroll
          for (int i = 0; i < 3; i++) mma16816(sm[i & 1], qa[i].x, 0u, qa[i].y, 0u, kk[i].x, kk[i].y);
        }
        const uint32_t dl = sb + OFF_S + rank * 1280 + lane * 8;
        const uint32_t s0 = __float_as_uint(sc[0][0] + sc[1][0]), s1 = __float_as_uint(sc[0][1] + sc[1][1]);
#pragma unroll
        for (int r = 0; r < 3; r++) st_async64(mapa(dl + aw * 256, r), s0, s1, mapa(bar_xs, r));
        if (aw == 3) {
          const uint32_t m0 = __float_as_uint(sm[0][0] + sm[1][0]), m1 = __float_as_uint(sm[0][1] + sm[1][1]);
#pragma unroll
          for (int r = 0; r < 3; r++) st_async64(mapa(dl + 1024, r), m0, m1, mapa(bar_xs, r));
        }
      }
      PROF(4);
      mbar_wait(bar_xs, par);
      PROF(6);
      float v[10];
      {
        const uint32_t sa = sb + OFF_S + lane * 8;
#pragma unroll
        for (int n = 0; n < 5; n++) {
          const uint2 a = lds64(sa + n * 256), b = lds64(sa + 1280 + n * 256), c = lds64(sa + 2560 + n * 256);
          v[2 * n] = __uint_as_float(a.x) + __uint_as_float(b.x) + __uint_as_float(c.x);
          v[2 * n + 1] = __uint_as_float(a.y) + __uint_as_float(b.y) + __uint_as_float(c.y);
        }
      }
      float mx = fmaxf(fmaxf(fmaxf(v[0], v[1]), fmaxf(v[2], v[3])), fmaxf(fmaxf(v[4], v[5]), fmaxf(v[6], v[7])));
      mx = fmaxf(mx, fmaxf(v[8], v[9]));
      mx = fmaxf(mx, __shfl_xor_sync(~0u, mx, 1));
      mx = fmaxf(mx, __shfl_xor_sync(~0u, mx, 2));
      const float kscale = 0.08838834764831845f * 1.4426950408889634f;
      const float mo = -mx * kscale;
#pragma unroll
      for (int i = 0; i < 10; i++) v[i] = ex2(fmaf(v[i], kscale, mo));
      float sum = ((v[0] + v[1]) + (v[2] + v[3])) + ((v[4] + v[5]) + (v[6] + v[7])) + (v[8] + v[9]);
      sum += __shfl_xor_sync(~0u, sum, 1);
      sum += __shfl_xor_sync(~0u, sum, 2);
      const float inv = __fdividef(1.f, sum);
      const uint32_t p0 = pack2(v[0] * inv, v[1] * inv), p1 = pack2(v[2] * inv, v[3] * inv), p2 = pack2(v[4] * inv, v[5] * inv),
                     p3 = pack2(v[6] * inv, v[7] * inv), p4 = pack2(v[8] * inv, v[9] * inv);
      PROF(7);
      mbar_wait(bar_xv, par);
      {
        float c[2][4], d[2][4];
        uint2 vm[2];
#pragma unroll
        for (int m = 0; m < 2; m++) vm[m] = lds64(sb + OFF_VM + (aw + 4 * m) * 256 + lane * 8);
#pragma unroll
        for (int m = 0; m < 2; m++) {
          c[m][0] = c[m][1] = c[m][2] = c[m][3] = 0.f; d[m][0] = d[m][1] = d[m][2] = d[m][3] = 0.f;
          mma16816(c[m], va[m][0][0], va[m][0][1], va[m][0][2], va[m][0][3], p0, p1);
          mma16816(d[m], va[m][1][0], va[m][1][1], va[m][1][2], va[m][1][3], p2, p3);
        }
#pragma unroll
        for (int m = 0; m < 2; m++) mma16816(c[m], vm[m].x, vm[m].y, 0u, 0u, p4, 0u);
#pragma unroll
        for (int m = 0; m < 2; m++) {
          const int mt = aw + 4 * m;
          const uint32_t b0 = movtrans(pack2(c[m][0] + d[m][0], c[m][1] + d[m][1]));
          const uint32_t b1 = movtrans(pack2(c[m][2] + d[m][2], c[m][3] + d[m][3]));
          sts64(sb + OFF_O + (mt >> 1) * 512 + lane * 16 + (mt & 1) * 8, b0, b1);
        }
      }
      uint4 w2a, w2b;
      const uint32_t w2p = sb + OFF_WO + (4 + aw) * 4096 + lane * 16;
      if (two) { w2a = lds128(w2p); w2b = lds128(w2p + 512); }
      PROF(8);
      bar_sync(8, 384);
      const uint32_t flag = ((s >> 1) & 1) ^ 1;
      {
        float c[4][4];
#pragma unroll
        for (int a = 0; a < 4; a++) c[a][0] = c[a][1] = c[a][2] = c[a][3] = 0.f;
        uint4 obn = lds128(sb + OFF_O + lane * 16);
#pragma unroll
        for (int i = 0; i < 4; i++) {
          const uint4 ob = obn;
          if (i < 3) obn = lds128(sb + OFF_O + (i + 1) * 512 + lane * 16);
          mma16816(c[0], wf[2 * i].x, wf[2 * i].y, wf[2 * i].z, wf[2 * i].w, ob.x, ob.y);
          mma16816(c[1], wf[2 * i + 1].x, wf[2 * i + 1].y, wf[2 * i + 1].z, wf[2 * i + 1].w, ob.z, ob.w);
          if (two) {
            const uint4 x = w2a, y = w2b;
            if (i < 3) { w2a = lds128(w2p + (2 * i + 2) * 512); w2b = lds128(w2p + (2 * i + 3) * 512); }
            mma16816(c[2], x.x, x.y, x.z, x.w, ob.x, ob.y);
            mma16816(c[3], y.x, y.y, y.z, y.w, ob.z, ob.w);
          }
        }
        float* dst0 = g_part + ((((size_t)par * 160 + (wt0 + 8 + aw) * 4 + jj) * 32 + head) * 8 + rho) * 4;
#pragma unroll
        for (int a = 0; a < 2; a++) {
          if (a == 0 || two) {
            uint32_t w[4];
#pragma unroll
            for (int e = 0; e < 4; e++) w[e] = (__float_as_uint(c[2 * a][e] + c[2 * a + 1][e]) & ~1u) | flag;
            stg_relaxed128(dst0 + a * (4 * 4 * 32 * 8 * 4), w[0], w[1], w[2], w[3]);
          }
        }
      }
      const uint32_t t_o = (uint32_t)clock();
      PROF(9);
      if (aw == 1 && lane == 0 && s + 2 < NSEG - 1) load_kv(s + 2);
      if (is_red) {
        const uint4* src = reinterpret_cast<const uint4*>(g_part) + ((size_t)par * 160 + unit) * 256 + lane;
        uint4 w[8];
        int guard = 0;
        while ((int)((uint32_t)clock() - t_o) < DELAY_A) { }
        while (true) {
#pragma unroll
          for (int i = 0; i < 8; i++) w[i] = ldg_relaxed128(src + i * 32);
          uint32_t a = ~0u, o = 0u;
#pragma unroll
          for (int i = 0; i < 8; i++) { a &= w[i].x & w[i].y & w[i].z & w[i].w; o |= w[i].x | w[i].y | w[i].z | w[i].w; }
          const bool ok = flag ? (a & 1u) : !(o & 1u);
          if (__all_sync(~0u, ok)) break;
          if (++guard > (1 << 22)) { g_err = 4; __trap(); }
        }
        PROF(10);
#define F_(i, m) __uint_as_float(w[i].m)
        float r0 = ((F_(0, x) + F_(1, x)) + (F_(2, x) + F_(3, x))) + ((F_(4, x) + F_(5, x)) + (F_(6, x) + F_(7, x)));
        float r1 = ((F_(0, y) + F_(1, y)) + (F_(2, y) + F_(3, y))) + ((F_(4, y) + F_(5, y)) + (F_(6, y) + F_(7, y)));
        float r2 = ((F_(0, z) + F_(1, z)) + (F_(2, z) + F_(3, z))) + ((F_(4, z) + F_(5, z)) + (F_(6, z) + F_(7, z)));
        float r3 = ((F_(0, w) + F_(1, w)) + (F_(2, w) + F_(3, w))) + ((F_(4, w) + F_(5, w)) + (F_(6, w) + F_(7, w)));
#undef F_
#pragma unroll
        for (int o = 8; o < 32; o <<= 1) {
          r0 += __shfl_xor_sync(~0u, r0, o); r1 += __shfl_xor_sync(~0u, r1, o);
          r2 += __shfl_xor_sync(~0u, r2, o); r3 += __shfl_xor_sync(~0u, r3, o);
        }
        if (lane < 16) {
          const int t = unit >> 2, j = unit & 3, e = lane >> 3, r8 = lane & 7;
          const int w0 = ((t >> 1) * 32 + (2 * j + e) * 4 + (t & 1) * 2) * 4 + r8;
          stg_relaxed32(g_memb + ((s + 1) & 3) * 2560 + w0, e ? pack2(r1, r3) : pack2(r0, r2));
          stg_relaxed32(g_memb + ((s + 3) & 3) * 2560 + w0, ~0u);
        }
      }
    }
    bar_sync(6, 384);
  }
  asm volatile("barrier.cluster.arrive;\nbarrier.cluster.wait;" ::: "memory");
}

__global__ void __launch_bounds__(64) attn_kernel() {
  __shared__ __align__(1024) uint8_t sm[8192 * 3 + 4096 + 16];
  const uint32_t sb = smem_u32(sm);
  const uint32_t sQ = sb, sK = sb + 8192, sV = sb + 16384, sKm = sb + 24576, sVm = sKm + 2048, bar = sVm + 2048;
  const int seg = blockIdx.x >> 5, head = blockIdx.x & 31;
  const int warp = threadIdx.x >> 5, lane = threadIdx.x & 31;
  if (threadIdx.x == 0) {
    mbar_init(bar, 1);
    asm volatile("fence.mbarrier_init.release.cluster;" ::: "memory");
    mbar_expect_tx(bar, 8192 * 3 + 4096);
    const size_t off = ((size_t)head * S_TOK + seg * SEG) * DH;
    bulk_g2s(sQ, g_q + off, 8192, bar); bulk_g2s(sK, g_k + off, 8192, bar); bulk_g2s(sV, g_v + off, 8192, bar);
    const size_t offm = (size_t)(seg * NH + head) * NMEM * DH;
    bulk_g2s(sKm, g_km + offm, 2048, bar); bulk_g2s(sVm, g_vm + offm, 2048, bar);
  }
  __syncthreads();
  mbar_wait(bar, 0);
  const int rho = lane >> 2, jj = lane & 3;
  float sc[5][4];
#pragma unroll
  for (int n = 0; n < 5; n++) sc[n][0] = sc[n][1] = sc[n][2] = sc[n][3] = 0.f;
#pragma unroll
  for (int ks = 0; ks < 8; ks++) {
    uint32_t a[4];
    {
      const int row = warp * 16 + ((lane >> 3) & 1) * 8 + (lane & 7), ch = 2 * ks + (lane >> 4);
      ldsm4(a, sQ + row * 256 + ((ch ^ (row & 7)) << 4));
    }
#pragma unroll
    for (int n = 0; n < 4; n += 2) {
      uint32_t kf[4];
      const int key = (n + (lane >> 4)) * 8 + (lane & 7), ch = 2 * ks + ((lane >> 3) & 1);
      ldsm4(kf, sK + key * 256 + ((ch ^ (key & 7)) << 4));
      mma16816(sc[n], a[0], a[1], a[2], a[3], kf[0], kf[1]);
      mma16816(sc[n + 1], a[0], a[1], a[2], a[3], kf[2], kf[3]);
    }
    uint32_t mf[2];
    {
      const int key = lane & 7, ch = 2 * ks + ((lane >> 3) & 1);
      ldsm2(mf, sKm + key * 256 + ((ch ^ key) << 4));
    }
    mma16816(sc[4], a[0], a[1], a[2], a[3], mf[0], mf[1]);
  }
  uint32_t pa[3][4];
  {
    float mx0 = -3.0e38f, mx1 = -3.0e38f;
    const int q0 = warp * 16 + rho, q1 = q0 + 8;
#pragma unroll
    for (int n = 0; n < 5; n++) {
#pragma unroll
      for (int e = 0; e < 4; e++) {
        float v = bfr(bfr(sc[n][e]) * 0.08838834764831845f);
        if (n < 4) { const int key = n * 8 + jj * 2 + (e & 1); if (key > ((e & 2) ? q1 : q0)) v = -1.0e9f; }
        sc[n][e] = v;
        if (e & 2) mx1 = fmaxf(mx1, v); else mx0 = fmaxf(mx0, v);
      }
    }
    mx0 = fmaxf(mx0, __shfl_xor_sync(~0u, mx0, 1)); mx0 = fmaxf(mx0, __shfl_xor_sync(~0u, mx0, 2));
    mx1 = fmaxf(mx1, __shfl_xor_sync(~0u, mx1, 1)); mx1 = fmaxf(mx1, __shfl_xor_sync(~0u, mx1, 2));
    float s0 = 0.f, s1 = 0.f;
#pragma unroll
    for (int n = 0; n < 5; n++) {
      sc[n][0] = __expf(sc[n][0] - mx0); sc[n][1] = __expf(sc[n][1] - mx0); s0 += sc[n][0] + sc[n][1];
      sc[n][2] = __expf(sc[n][2] - mx1); sc[n][3] = __expf(sc[n][3] - mx1); s1 += sc[n][2] + sc[n][3];
    }
    s0 += __shfl_xor_sync(~0u, s0, 1); s0 += __shfl_xor_sync(~0u, s0, 2);
    s1 += __shfl_xor_sync(~0u, s1, 1); s1 += __shfl_xor_sync(~0u, s1, 2);
    const float i0 = 1.f / s0, i1 = 1.f / s1;
#pragma unroll
    for (int ks = 0; ks < 2; ks++) {
      pa[ks][0] = pack2(sc[2 * ks][0] * i0, sc[2 * ks][1] * i0); pa[ks][1] = pack2(sc[2 * ks][2] * i1, sc[2 * ks][3] * i1);
      pa[ks][2] = pack2(sc[2 * ks + 1][0] * i0, sc[2 * ks + 1][1] * i0); pa[ks][3] = pack2(sc[2 * ks + 1][2] * i1, sc[2 * ks + 1][3] * i1);
    }
    pa[2][0] = pack2(sc[4][0] * i0, sc[4][1] * i0); pa[2][1] = pack2(sc[4][2] * i1, sc[4][3] * i1); pa[2][2] = 0; pa[2][3] = 0;
  }
  __syncwarp();
  const int srow = ((lane >> 3) & 1) * 8 + (lane & 7), schunk = lane >> 4;
#pragma unroll
  for (int n = 0; n < 16; n += 2) {
    float o0[4] = {0.f, 0.f, 0.f, 0.f}, o1[4] = {0.f, 0.f, 0.f, 0.f};
#pragma unroll
    for (int ks = 0; ks < 2; ks++) {
      uint32_t vf[4];
      const int key = ks * 16 + ((lane >> 3) & 1) * 8 + (lane & 7), ch = n + (lane >> 4);
      ldsm4t(vf, sV + key * 256 + ((ch ^ (key & 7)) << 4));
      mma16816(o0, pa[ks][0], pa[ks][1], pa[ks][2], pa[ks][3], vf[0], vf[1]);
      mma16816(o1, pa[ks][0], pa[ks][1], pa[ks][2], pa[ks][3], vf[2], vf[3]);
    }
    uint32_t mf[2];
    {
      const int key = lane & 7, ch = n + ((lane >> 3) & 1);
      ldsm2t(mf, sVm + key * 256 + ((ch ^ key) << 4));
    }
    mma16816(o0, pa[2][0], pa[2][1], 0u, 0u, mf[0], 0u);
    mma16816(o1, pa[2][0], pa[2][1], 0u, 0u, mf[1], 0u);
    stsm4(sQ + (warp * 16 + srow) * 256 + (((n + schunk) ^ (srow & 7)) << 4), pack2(o0[0], o0[1]), pack2(o0[2], o0[3]), pack2(o1[0], o1[1]), pack2(o1[2], o1[3]));
  }
  __syncwarp();
#pragma unroll
  for (int i = 0; i < 8; i++) {
    const int r = i * 2 + (lane >> 4), ch = lane & 15;
    uint4 a = lds128(sQ + (warp * 16 + r) * 256 + ((ch ^ (r & 7)) << 4));
    *reinterpret_cast<uint4*>(g_o + (size_t)(seg * SEG + warp * 16 + r) * HD + head * DH + ch * 8) = a;
  }
}

typedef CUresult (*EncodeFn)(CUtensorMap*, CUtensorMapDataType, cuuint32_t, void*, const cuuint64_t*, const cuuint64_t*,
                             const cuuint32_t*, const cuuint32_t*, CUtensorMapInterleave, CUtensorMapSwizzle,
                             CUtensorMapL2promotion, CUtensorMapFloatOOBfill);
static EncodeFn s_encode = nullptr;
static cudaStream_t s_rec;
static cudaEvent_t s_evFork, s_evJoin;
#define SHADOW_CTAS 36

static CUtensorMap make_map(const void* ptr, uint64_t inner, uint64_t outer, uint32_t box_inner, uint32_t box_outer, bool swz = true) {
  CUtensorMap m;
  cuuint64_t dims[2] = {inner, outer};
  cuuint64_t strides[1] = {inner * 2};
  cuuint32_t box[2] = {box_inner, box_outer};
  cuuint32_t es[2] = {1, 1};
  s_encode(&m, CU_TENSOR_MAP_DATA_TYPE_BFLOAT16, 2, const_cast<void*>(ptr), dims, strides, box, es, CU_TENSOR_MAP_INTERLEAVE_NONE,
           swz ? CU_TENSOR_MAP_SWIZZLE_128B : CU_TENSOR_MAP_SWIZZLE_NONE, CU_TENSOR_MAP_L2_PROMOTION_L2_256B, CU_TENSOR_MAP_FLOAT_OOB_FILL_NONE);
  return m;
}
template <class T> static void* sym_addr(T& sym) { void* p = nullptr; cudaGetSymbolAddress(&p, sym); return p; }

extern "C" void kernel_launch(void* const* d_in, const int* in_sizes, int n_in, void* d_out, int out_size) {
  const bf16* x = (const bf16*)d_in[0];
  const bf16* mem0 = (const bf16*)d_in[1];
  const bf16* Wq = (const bf16*)d_in[2];
  const bf16* Wk = (const bf16*)d_in[3];
  const bf16* Wv = (const bf16*)d_in[4];
  const bf16* Wo = (const bf16*)d_in[5];
  const bf16* w_gate = (const bf16*)d_in[8];
  const bf16* w_up = (const bf16*)d_in[9];
  const bf16* w_down = (const bf16*)d_in[10];
  const bf16* cvec = (const bf16*)d_in[11];
  const bf16* w_mod = (const bf16*)d_in[12];
  bf16* out = (bf16*)d_out;

  static bool init = false;
  static void *p_h, *p_o, *p_x1, *p_h2, *p_act, *p_k;
  if (!init) {
    cudaDriverEntryPointQueryResult qr;
    void* fn = nullptr;
    cudaGetDriverEntryPoint("cuTensorMapEncodeTiled", &fn, cudaEnableDefault, &qr);
    s_encode = (EncodeFn)fn;
    p_h = sym_addr(g_h); p_o = sym_addr(g_o); p_x1 = sym_addr(g_x1); p_h2 = sym_addr(g_h2); p_act = sym_addr(g_act); p_k = sym_addr(g_k);
    cudaFuncSetAttribute(gemm_kernel<256, EPI_QKV>, cudaFuncAttributeMaxDynamicSharedMemorySize, GemmCfg<256>::SMEM);
    cudaFuncSetAttribute(gemm_kernel<128, EPI_RES>, cudaFuncAttributeMaxDynamicSharedMemorySize, GemmCfg<128>::SMEM);
    cudaFuncSetAttribute(gemm_kernel<128, EPI_GEGLU>, cudaFuncAttributeMaxDynamicSharedMemorySize, GemmCfg<128>::SMEM);
    cudaFuncSetAttribute(rec_kernel, cudaFuncAttributeMaxDynamicSharedMemorySize, rc::SMEM);
    cudaFuncAttributes fa;
    cudaFuncGetAttributes(&fa, mod_kernel); cudaFuncGetAttributes(&fa, ln_kernel); cudaFuncGetAttributes(&fa, attn_kernel);
    cudaFuncGetAttributes(&fa, rec_kernel); cudaFuncGetAttributes(&fa, gemm_kernel<256, EPI_QKV>);
    cudaFuncGetAttributes(&fa, gemm_kernel<128, EPI_RES>); cudaFuncGetAttributes(&fa, gemm_kernel<128, EPI_GEGLU>);
    int lo = 0, hi = 0;
    cudaDeviceGetStreamPriorityRange(&lo, &hi);
    cudaStreamCreateWithPriority(&s_rec, cudaStreamNonBlocking, hi);
    cudaEventCreateWithFlags(&s_evFork, cudaEventDisableTiming);
    cudaEventCreateWithFlags(&s_evJoin, cudaEventDisableTiming);
    init = true;
  }
  CUtensorMap mA_h = make_map(p_h, DM, S_TOK, 64, 128);
  CUtensorMap mB_q = make_map(Wq, HD, DM, 64, 64), mB_k = make_map(Wk, HD, DM, 64, 64), mB_v = make_map(Wv, HD, DM, 64, 64);
  CUtensorMap mA_o = make_map(p_o, HD, S_TOK, 64, 128), mB_o = make_map(Wo, DM, HD, 64, 64);
  CUtensorMap mA_h2 = make_map(p_h2, DM, S_TOK, 64, 128);
  CUtensorMap mB_g = make_map(w_gate, FF, DM, 64, 64), mB_u = make_map(w_up, FF, DM, 64, 64);
  CUtensorMap mA_act = make_map(p_act, FF, S_TOK, 64, 128), mB_d = make_map(w_down, DM, FF, 64, 64);

  cudaStream_t st = cudaStreamPerThread;
  mod_kernel<<<120, 256, 0, st>>>(cvec, w_mod, mem0);
  cudaEventRecord(s_evFork, st);
  cudaStreamWaitEvent(s_rec, s_evFork, 0);
  rec_kernel<<<rc::NCTA, 384, rc::SMEM, s_rec>>>(Wq, Wk, Wv, Wo);
  cudaEventRecord(s_evJoin, s_rec);
  ln_kernel<<<S_TOK / 8, 256, 0, st>>>(x, (bf16*)p_h, 0, DM, rc::NCTA);
  {
    GemmP p{16, 32, 10, 16, nullptr, nullptr, 0, 1, 1};
    gemm_kernel<256, EPI_QKV><<<SHADOW_CTAS, 288, GemmCfg<256>::SMEM, st>>>(mA_h, mB_q, mB_k, mB_v, p);
    GemmP q{16, 16, 10, 0, nullptr, nullptr, 0, 0, 0};
    gemm_kernel<256, EPI_QKV><<<SHADOW_CTAS, 288, GemmCfg<256>::SMEM, st>>>(mA_h, mB_q, mB_k, mB_v, q);
  }
  cudaStreamWaitEvent(st, s_evJoin, 0);
  attn_kernel<<<NSEG * NH, 64, 0, st>>>();
  {
    GemmP p{16, 5, 64, 0, x, (bf16*)p_x1, 2 * DM, 0, 0};
    gemm_kernel<128, EPI_RES><<<80, 288, GemmCfg<128>::SMEM, st>>>(mA_o, mB_o, mB_o, mB_o, p);
  }
  ln_kernel<<<S_TOK / 8, 256, 0, st>>>((const bf16*)p_x1, (bf16*)p_h2, 3 * DM, 4 * DM, 0);
  {
    GemmP p{16, 27, 10, 0, nullptr, nullptr, 0, 0, 0};
    gemm_kernel<128, EPI_GEGLU><<<132, 288, GemmCfg<128>::SMEM, st>>>(mA_h2, mB_g, mB_u, mB_u, p);
  }
  {
    GemmP p{16, 5, 27, 0, (const bf16*)p_x1, out, 5 * DM, 0, 0};
    gemm_kernel<128, EPI_RES><<<80, 288, GemmCfg<128>::SMEM, st>>>(mA_act, mB_d, mB_d, mB_d, p);
  }
}
```

```cpp
#include <cuda_runtime.h>
#include <cuda_bf16.h>
#include <cuda.h>
#include <stdint.h>

typedef __nv_bfloat16 bf16;

constexpr int S_TOK = 2048, DM = 640, NH = 32, DH = 128, NMEM = 8, SEG = 32, NSEG = 64, FF = 1728;
constexpr int HD = NH * DH;

__device__ float g_mod[6 * DM];
__device__ __align__(1024) bf16 g_h[S_TOK * DM];
__device__ __align__(1024) bf16 g_q[NH * S_TOK * DH];
__device__ __align__(1024) bf16 g_k[NH * S_TOK * DH];
__device__ __align__(1024) bf16 g_v[NH * S_TOK * DH];
__device__ __align__(1024) bf16 g_km[NSEG * NH * NMEM * DH];
__device__ __align__(1024) bf16 g_vm[NSEG * NH * NMEM * DH];
__device__ __align__(1024) bf16 g_o[S_TOK * HD];
__device__ __align__(1024) bf16 g_x1[S_TOK * DM];
__device__ __align__(1024) bf16 g_h2[S_TOK * DM];
__device__ __align__(1024) bf16 g_act[S_TOK * FF];
__device__ __align__(1024) float g_part[2 * 40 * 8 * 32 * 16];
__device__ __align__(1024) uint32_t g_memb[4 * 2560];
__device__ int g_err;
__device__ unsigned g_kvflag[16 * 96];
__device__ unsigned g_resident;
__device__ unsigned g_ready;
__device__ unsigned g_resident2;
__device__ unsigned g_oflag[16];
__device__ unsigned g_mflag[NSEG * NH];

#define TL_START(id)
#define TL_END(id)
__device__ __forceinline__ uint32_t smem_u32(const void* p) { return (uint32_t)__cvta_generic_to_shared(p); }
__device__ __forceinline__ uint32_t pack2(float lo, float hi) {
  uint32_t r; asm("cvt.rn.bf16x2.f32 %0, %1, %2;" : "=r"(r) : "f"(hi), "f"(lo)); return r;
}
__device__ __forceinline__ float bfr(float x) { return __uint_as_float(pack2(0.f, x) & 0xffff0000u); }
__device__ __forceinline__ float lo2f(uint32_t v) { return __uint_as_float(v << 16); }
__device__ __forceinline__ float hi2f(uint32_t v) { return __uint_as_float(v & 0xffff0000u); }

__device__ __forceinline__ void mbar_init(uint32_t bar, uint32_t cnt) {
  asm volatile("mbarrier.init.shared::cta.b64 [%0], %1;" ::"r"(bar), "r"(cnt) : "memory");
}
__device__ __forceinline__ void mbar_expect_tx(uint32_t bar, uint32_t bytes) {
  asm volatile("mbarrier.arrive.expect_tx.shared::cta.b64 _, [%0], %1;" ::"r"(bar), "r"(bytes) : "memory");
}
__device__ __forceinline__ void mbar_arrive(uint32_t bar) {
  asm volatile("mbarrier.arrive.shared::cta.b64 _, [%0];" ::"r"(bar) : "memory");
}
__device__ __forceinline__ bool mbar_try(uint32_t bar, uint32_t parity) {
  uint32_t ok;
  asm volatile("{\n.reg .pred p;\nmbarrier.try_wait.parity.shared::cta.b64 p, [%1], %2;\nselp.u32 %0,1,0,p;\n}"
               : "=r"(ok) : "r"(bar), "r"(parity) : "memory");
  return ok != 0;
}
__device__ __forceinline__ void mbar_wait(uint32_t bar, uint32_t parity) {
  int guard = 0;
  while (!mbar_try(bar, parity)) { if (++guard > (1 << 24)) { g_err = 1; __trap(); } }
}
__device__ __forceinline__ void mbar_wait_cluster(uint32_t bar, uint32_t parity) {
  int guard = 0; uint32_t ok;
  do {
    asm volatile("{\n.reg .pred p;\nmbarrier.try_wait.parity.acquire.cluster.shared::cta.b64 p, [%1], %2;\nselp.u32 %0,1,0,p;\n}"
                 : "=r"(ok) : "r"(bar), "r"(parity) : "memory");
    if (++guard > (1 << 24)) { g_err = 2; __trap(); }
  } while (!ok);
}
__device__ __forceinline__ void tma_load_2d(uint32_t dst, const CUtensorMap* map, int x, int y, uint32_t bar) {
  asm volatile("cp.async.bulk.tensor.2d.shared::cluster.global.mbarrier::complete_tx::bytes [%0], [%1, {%3, %4}], [%2];"
               ::"r"(dst), "l"((uint64_t)map), "r"(bar), "r"(x), "r"(y) : "memory");
}
__device__ __forceinline__ void bulk_g2s(uint32_t dst, const void* src, uint32_t bytes, uint32_t bar) {
  asm volatile("cp.async.bulk.shared::cluster.global.mbarrier::complete_tx::bytes [%0], [%1], %2, [%3];"
               ::"r"(dst), "l"((uint64_t)src), "r"(bytes), "r"(bar) : "memory");
}
__device__ __forceinline__ void bulk_s2g(void* dst, uint32_t src, uint32_t bytes) {
  asm volatile("cp.async.bulk.global.shared::cta.bulk_group [%0], [%1], %2;" ::"l"((uint64_t)dst), "r"(src), "r"(bytes) : "memory");
}
__device__ __forceinline__ void bulk_commit() { asm volatile("cp.async.bulk.commit_group;" ::: "memory"); }
__device__ __forceinline__ void bulk_wait_read0() { asm volatile("cp.async.bulk.wait_group.read 0;" ::: "memory"); }
__device__ __forceinline__ void bulk_wait0() { asm volatile("cp.async.bulk.wait_group 0;" ::: "memory"); }
__device__ __forceinline__ void fence_async_smem() { asm volatile("fence.proxy.async.shared::cta;" ::: "memory"); }
__device__ __forceinline__ void wg_fence() { asm volatile("wgmma.fence.sync.aligned;" ::: "memory"); }
__device__ __forceinline__ void wg_commit() { asm volatile("wgmma.commit_group.sync.aligned;" ::: "memory"); }
template <int N> __device__ __forceinline__ void wg_wait() { asm volatile("wgmma.wait_group.sync.aligned %0;" ::"n"(N) : "memory"); }
__device__ __forceinline__ void bar_sync(int id, int n) { asm volatile("bar.sync %0, %1;" ::"r"(id), "r"(n) : "memory"); }

__device__ __forceinline__ void mma16816(float* c, uint32_t a0, uint32_t a1, uint32_t a2, uint32_t a3, uint32_t b0, uint32_t b1) {
  asm volatile("mma.sync.aligned.m16n8k16.row.col.f32.bf16.bf16.f32 {%0,%1,%2,%3},{%4,%5,%6,%7},{%8,%9},{%0,%1,%2,%3};"
               : "+f"(c[0]), "+f"(c[1]), "+f"(c[2]), "+f"(c[3]) : "r"(a0), "r"(a1), "r"(a2), "r"(a3), "r"(b0), "r"(b1));
}
__device__ __forceinline__ void ldsm4(uint32_t* r, uint32_t addr) {
  asm volatile("ldmatrix.sync.aligned.m8n8.x4.shared.b16 {%0,%1,%2,%3}, [%4];"
               : "=r"(r[0]), "=r"(r[1]), "=r"(r[2]), "=r"(r[3]) : "r"(addr) : "memory");
}
__device__ __forceinline__ void ldsm4t(uint32_t* r, uint32_t addr) {
  asm volatile("ldmatrix.sync.aligned.m8n8.x4.trans.shared.b16 {%0,%1,%2,%3}, [%4];"
               : "=r"(r[0]), "=r"(r[1]), "=r"(r[2]), "=r"(r[3]) : "r"(addr) : "memory");
}
__device__ __forceinline__ void ldsm2(uint32_t* r, uint32_t addr) {
  asm volatile("ldmatrix.sync.aligned.m8n8.x2.shared.b16 {%0,%1}, [%2];" : "=r"(r[0]), "=r"(r[1]) : "r"(addr) : "memory");
}
__device__ __forceinline__ void ldsm2t(uint32_t* r, uint32_t addr) {
  asm volatile("ldmatrix.sync.aligned.m8n8.x2.trans.shared.b16 {%0,%1}, [%2];" : "=r"(r[0]), "=r"(r[1]) : "r"(addr) : "memory");
}
__device__ __forceinline__ void stsm4(uint32_t addr, uint32_t r0, uint32_t r1, uint32_t r2, uint32_t r3) {
  asm volatile("stmatrix.sync.aligned.m8n8.x4.shared.b16 [%0], {%1,%2,%3,%4};" ::"r"(addr), "r"(r0), "r"(r1), "r"(r2), "r"(r3) : "memory");
}
__device__ __forceinline__ uint32_t movtrans(uint32_t a) {
  uint32_t d; asm volatile("movmatrix.sync.aligned.m8n8.trans.b16 %0, %1;" : "=r"(d) : "r"(a)); return d;
}
__device__ __forceinline__ uint4 lds128(uint32_t a) {
  uint4 v; asm volatile("ld.shared.v4.u32 {%0,%1,%2,%3}, [%4];" : "=r"(v.x), "=r"(v.y), "=r"(v.z), "=r"(v.w) : "r"(a) : "memory"); return v;
}
__device__ __forceinline__ float4 lds128f(uint32_t a) {
  float4 v; asm volatile("ld.shared.v4.f32 {%0,%1,%2,%3}, [%4];" : "=f"(v.x), "=f"(v.y), "=f"(v.z), "=f"(v.w) : "r"(a) : "memory"); return v;
}
__device__ __forceinline__ uint2 lds64(uint32_t a) {
  uint2 v; asm volatile("ld.shared.v2.u32 {%0,%1}, [%2];" : "=r"(v.x), "=r"(v.y) : "r"(a) : "memory"); return v;
}
__device__ __forceinline__ void sts128(uint32_t a, uint32_t x, uint32_t y, uint32_t z, uint32_t w) {
  asm volatile("st.shared.v4.u32 [%0], {%1,%2,%3,%4};" ::"r"(a), "r"(x), "r"(y), "r"(z), "r"(w) : "memory");
}
__device__ __forceinline__ void sts128f(uint32_t a, const float* c) {
  asm volatile("st.shared.v4.f32 [%0], {%1,%2,%3,%4};" ::"r"(a), "f"(c[0]), "f"(c[1]), "f"(c[2]), "f"(c[3]) : "memory");
}
__device__ __forceinline__ void sts64(uint32_t a, uint32_t x, uint32_t y) {
  asm volatile("st.shared.v2.u32 [%0], {%1,%2};" ::"r"(a), "r"(x), "r"(y) : "memory");
}
__device__ __forceinline__ uint4 ldg_relaxed128(const void* p) {
  uint4 v; asm volatile("ld.relaxed.gpu.global.v4.u32 {%0,%1,%2,%3}, [%4];" : "=r"(v.x), "=r"(v.y), "=r"(v.z), "=r"(v.w) : "l"(p) : "memory"); return v;
}
__device__ __forceinline__ void stg_relaxed128(void* p, uint32_t x, uint32_t y, uint32_t z, uint32_t w) {
  asm volatile("st.relaxed.gpu.global.v4.u32 [%0], {%1,%2,%3,%4};" ::"l"(p), "r"(x), "r"(y), "r"(z), "r"(w) : "memory");
}
__device__ __forceinline__ void stg_relaxed32(void* p, uint32_t x) {
  asm volatile("st.relaxed.gpu.global.u32 [%0], %1;" ::"l"(p), "r"(x) : "memory");
}
__device__ __forceinline__ uint32_t ld_acquire32(const void* p) {
  uint32_t v; asm volatile("ld.acquire.gpu.global.u32 %0, [%1];" : "=r"(v) : "l"(p) : "memory"); return v;
}
__device__ __forceinline__ void red_release_add(void* p, uint32_t v) {
  asm volatile("red.release.gpu.global.add.u32 [%0], %1;" ::"l"(p), "r"(v) : "memory");
}
__device__ __forceinline__ void fence_async_all() { asm volatile("fence.proxy.async;" ::: "memory"); }
__device__ __forceinline__ uint32_t mapa(uint32_t a, uint32_t rank) {
  uint32_t r; asm volatile("mapa.shared::cluster.u32 %0, %1, %2;" : "=r"(r) : "r"(a), "r"(rank)); return r;
}
__device__ __forceinline__ void st_async128(uint32_t a, uint32_t x, uint32_t y, uint32_t z, uint32_t w, uint32_t bar) {
  asm volatile("st.async.weak.shared::cluster.mbarrier::complete_tx::bytes.v4.u32 [%0], {%1,%2,%3,%4}, [%5];"
               ::"r"(a), "r"(x), "r"(y), "r"(z), "r"(w), "r"(bar) : "memory");
}
__device__ __forceinline__ void st_async64(uint32_t a, uint32_t x, uint32_t y, uint32_t bar) {
  asm volatile("st.async.weak.shared::cluster.mbarrier::complete_tx::bytes.v2.u32 [%0], {%1,%2}, [%3];"
               ::"r"(a), "r"(x), "r"(y), "r"(bar) : "memory");
}
__device__ __forceinline__ void cp_async16(uint32_t dst, const void* src) {
  asm volatile("cp.async.cg.shared.global [%0], [%1], 16;" ::"r"(dst), "l"(src) : "memory");
}
__device__ __forceinline__ void cp_async_wait_all() { asm volatile("cp.async.wait_all;" ::: "memory"); }

__device__ __forceinline__ void wgmma_n128(float* d, uint64_t da, uint64_t db, int scale_d) {
  asm volatile("{\n.reg .pred p;\nsetp.ne.b32 p, %66, 0;\n"
    "wgmma.mma_async.sync.aligned.m64n128k16.f32.bf16.bf16 {%0,%1,%2,%3,%4,%5,%6,%7,%8,%9,%10,%11,%12,%13,%14,%15,%16,%17,%18,%19,%20,%21,%22,%23,%24,%25,%26,%27,%28,%29,%30,%31,%32,%33,%34,%35,%36,%37,%38,%39,%40,%41,%42,%43,%44,%45,%46,%47,%48,%49,%50,%51,%52,%53,%54,%55,%56,%57,%58,%59,%60,%61,%62,%63}, %64, %65, p, 1, 1, 0, 1;\n}\n"
    : "+f"(d[0]),"+f"(d[1]),"+f"(d[2]),"+f"(d[3]),"+f"(d[4]),"+f"(d[5]),"+f"(d[6]),"+f"(d[7]),"+f"(d[8]),"+f"(d[9]),"+f"(d[10]),"+f"(d[11]),"+f"(d[12]),"+f"(d[13]),"+f"(d[14]),"+f"(d[15]),"+f"(d[16]),"+f"(d[17]),"+f"(d[18]),"+f"(d[19]),"+f"(d[20]),"+f"(d[21]),"+f"(d[22]),"+f"(d[23]),"+f"(d[24]),"+f"(d[25]),"+f"(d[26]),"+f"(d[27]),"+f"(d[28]),"+f"(d[29]),"+f"(d[30]),"+f"(d[31]),"+f"(d[32]),"+f"(d[33]),"+f"(d[34]),"+f"(d[35]),"+f"(d[36]),"+f"(d[37]),"+f"(d[38]),"+f"(d[39]),"+f"(d[40]),"+f"(d[41]),"+f"(d[42]),"+f"(d[43]),"+f"(d[44]),"+f"(d[45]),"+f"(d[46]),"+f"(d[47]),"+f"(d[48]),"+f"(d[49]),"+f"(d[50]),"+f"(d[51]),"+f"(d[52]),"+f"(d[53]),"+f"(d[54]),"+f"(d[55]),"+f"(d[56]),"+f"(d[57]),"+f"(d[58]),"+f"(d[59]),"+f"(d[60]),"+f"(d[61]),"+f"(d[62]),"+f"(d[63])
    : "l"(da), "l"(db), "r"(scale_d));
}

__device__ __forceinline__ void wgmma_n256(float* d, uint64_t da, uint64_t db, int scale_d) {
  asm volatile("{\n.reg .pred p;\nsetp.ne.b32 p, %130, 0;\n"
    "wgmma.mma_async.sync.aligned.m64n256k16.f32.bf16.bf16 {%0,%1,%2,%3,%4,%5,%6,%7,%8,%9,%10,%11,%12,%13,%14,%15,%16,%17,%18,%19,%20,%21,%22,%23,%24,%25,%26,%27,%28,%29,%30,%31,%32,%33,%34,%35,%36,%37,%38,%39,%40,%41,%42,%43,%44,%45,%46,%47,%48,%49,%50,%51,%52,%53,%54,%55,%56,%57,%58,%59,%60,%61,%62,%63,%64,%65,%66,%67,%68,%69,%70,%71,%72,%73,%74,%75,%76,%77,%78,%79,%80,%81,%82,%83,%84,%85,%86,%87,%88,%89,%90,%91,%92,%93,%94,%95,%96,%97,%98,%99,%100,%101,%102,%103,%104,%105,%106,%107,%108,%109,%110,%111,%112,%113,%114,%115,%116,%117,%118,%119,%120,%121,%122,%123,%124,%125,%126,%127}, %128, %129, p, 1, 1, 0, 1;\n}\n"
    : "+f"(d[0]),"+f"(d[1]),"+f"(d[2]),"+f"(d[3]),"+f"(d[4]),"+f"(d[5]),"+f"(d[6]),"+f"(d[7]),"+f"(d[8]),"+f"(d[9]),"+f"(d[10]),"+f"(d[11]),"+f"(d[12]),"+f"(d[13]),"+f"(d[14]),"+f"(d[15]),"+f"(d[16]),"+f"(d[17]),"+f"(d[18]),"+f"(d[19]),"+f"(d[20]),"+f"(d[21]),"+f"(d[22]),"+f"(d[23]),"+f"(d[24]),"+f"(d[25]),"+f"(d[26]),"+f"(d[27]),"+f"(d[28]),"+f"(d[29]),"+f"(d[30]),"+f"(d[31]),"+f"(d[32]),"+f"(d[33]),"+f"(d[34]),"+f"(d[35]),"+f"(d[36]),"+f"(d[37]),"+f"(d[38]),"+f"(d[39]),"+f"(d[40]),"+f"(d[41]),"+f"(d[42]),"+f"(d[43]),"+f"(d[44]),"+f"(d[45]),"+f"(d[46]),"+f"(d[47]),"+f"(d[48]),"+f"(d[49]),"+f"(d[50]),"+f"(d[51]),"+f"(d[52]),"+f"(d[53]),"+f"(d[54]),"+f"(d[55]),"+f"(d[56]),"+f"(d[57]),"+f"(d[58]),"+f"(d[59]),"+f"(d[60]),"+f"(d[61]),"+f"(d[62]),"+f"(d[63]),"+f"(d[64]),"+f"(d[65]),"+f"(d[66]),"+f"(d[67]),"+f"(d[68]),"+f"(d[69]),"+f"(d[70]),"+f"(d[71]),"+f"(d[72]),"+f"(d[73]),"+f"(d[74]),"+f"(d[75]),"+f"(d[76]),"+f"(d[77]),"+f"(d[78]),"+f"(d[79]),"+f"(d[80]),"+f"(d[81]),"+f"(d[82]),"+f"(d[83]),"+f"(d[84]),"+f"(d[85]),"+f"(d[86]),"+f"(d[87]),"+f"(d[88]),"+f"(d[89]),"+f"(d[90]),"+f"(d[91]),"+f"(d[92]),"+f"(d[93]),"+f"(d[94]),"+f"(d[95]),"+f"(d[96]),"+f"(d[97]),"+f"(d[98]),"+f"(d[99]),"+f"(d[100]),"+f"(d[101]),"+f"(d[102]),"+f"(d[103]),"+f"(d[104]),"+f"(d[105]),"+f"(d[106]),"+f"(d[107]),"+f"(d[108]),"+f"(d[109]),"+f"(d[110]),"+f"(d[111]),"+f"(d[112]),"+f"(d[113]),"+f"(d[114]),"+f"(d[115]),"+f"(d[116]),"+f"(d[117]),"+f"(d[118]),"+f"(d[119]),"+f"(d[120]),"+f"(d[121]),"+f"(d[122]),"+f"(d[123]),"+f"(d[124]),"+f"(d[125]),"+f"(d[126]),"+f"(d[127])
    : "l"(da), "l"(db), "r"(scale_d));
}

__global__ void __launch_bounds__(256) mod_kernel(const bf16* __restrict__ c, const bf16* __restrict__ w_mod) {
  __shared__ float s_c[DM];
  __shared__ float s_red[64][33];
  const int tid = threadIdx.x;
  TL_START(0);
  for (int i = tid; i < DM; i += 256) {
    float v = __bfloat162float(c[i]);
    s_c[i] = bfr(v / (1.f + __expf(-v)));
  }
  __syncthreads();
  {
    const int cg = tid & 3, kg = tid >> 2;
    const int col0 = blockIdx.x * 32 + cg * 8;
    float acc[8];
#pragma unroll
    for (int j = 0; j < 8; j++) acc[j] = 0.f;
    uint4 w[10];
#pragma unroll
    for (int i = 0; i < 10; i++) w[i] = *reinterpret_cast<const uint4*>(w_mod + (size_t)(kg * 10 + i) * (6 * DM) + col0);
#pragma unroll
    for (int i = 0; i < 10; i++) {
      float cv = s_c[kg * 10 + i];
      acc[0] += cv * lo2f(w[i].x); acc[1] += cv * hi2f(w[i].x);
      acc[2] += cv * lo2f(w[i].y); acc[3] += cv * hi2f(w[i].y);
      acc[4] += cv * lo2f(w[i].z); acc[5] += cv * hi2f(w[i].z);
      acc[6] += cv * lo2f(w[i].w); acc[7] += cv * hi2f(w[i].w);
    }
#pragma unroll
    for (int j = 0; j < 8; j++) s_red[kg][cg * 8 + j] = acc[j];
  }
  __syncthreads();
  if (tid < 32) {
    float s = 0.f;
    for (int i = 0; i < 64; i++) s += s_red[i][tid];
    g_mod[blockIdx.x * 32 + tid] = bfr(s);
  }
  TL_END(0);
}

__global__ void __launch_bounds__(256) ln_kernel(const bf16* __restrict__ x, bf16* __restrict__ out, int shift_off, int scale_off, unsigned gate, int reset) {
  const int warp = threadIdx.x >> 5, lane = threadIdx.x & 31;
  const int row = blockIdx.x * 8 + warp;
  TL_START(reset ? 6 : 1);
  const uint2* xr = reinterpret_cast<const uint2*>(x + (size_t)row * DM);
  float v[20];
#pragma unroll
  for (int i = 0; i < 5; i++) {
    uint2 u = xr[i * 32 + lane];
    v[i * 4 + 0] = lo2f(u.x); v[i * 4 + 1] = hi2f(u.x); v[i * 4 + 2] = lo2f(u.y); v[i * 4 + 3] = hi2f(u.y);
  }
  float s = 0.f;
#pragma unroll
  for (int i = 0; i < 20; i++) s += v[i];
#pragma unroll
  for (int o = 16; o; o >>= 1) s += __shfl_xor_sync(~0u, s, o);
  const float mean = s * (1.f / DM);
  float q = 0.f;
#pragma unroll
  for (int i = 0; i < 20; i++) { float d = v[i] - mean; q += d * d; }
#pragma unroll
  for (int o = 16; o; o >>= 1) q += __shfl_xor_sync(~0u, q, o);
  const float mb = bfr(mean);
  const float den = bfr(sqrtf(bfr(bfr(q * (1.f / DM)) + 1e-5f)));
  uint2* orow = reinterpret_cast<uint2*>(out + (size_t)row * DM);
#pragma unroll
  for (int i = 0; i < 5; i++) {
    const int col = (i * 32 + lane) * 4;
    float4 sh = *reinterpret_cast<const float4*>(g_mod + shift_off + col);
    float4 sc = *reinterpret_cast<const float4*>(g_mod + scale_off + col);
    float r0 = bfr(bfr(bfr(v[i * 4 + 0] - mb) / den) * bfr(1.f + sc.x)) + sh.x;
    float r1 = bfr(bfr(bfr(v[i * 4 + 1] - mb) / den) * bfr(1.f + sc.y)) + sh.y;
    float r2 = bfr(bfr(bfr(v[i * 4 + 2] - mb) / den) * bfr(1.f + sc.z)) + sh.z;
    float r3 = bfr(bfr(bfr(v[i * 4 + 3] - mb) / den) * bfr(1.f + sc.w)) + sh.w;
    orow[i * 32 + lane] = make_uint2(pack2(r0, r1), pack2(r2, r3));
  }
  if (reset) {
    const int gt = blockIdx.x * 256 + threadIdx.x;
    if (gt < 16 * 96) g_kvflag[gt] = 0;
    if (gt < NSEG * NH) g_mflag[gt] = 0;
    if (gt < 16) g_oflag[gt] = 0;
    if (gt == 0) { g_resident = 0; g_resident2 = 0; g_ready = 0; }
  }
  if (gate && blockIdx.x == 0 && threadIdx.x == 0) {
    for (int i = 0; i < 20000 && ld_acquire32(&g_resident) < gate; i++) __nanosleep(50);
  }
  TL_END(reset ? 6 : 1);
}

enum { EPI_QKV = 0, EPI_RES = 1, EPI_GEGLU = 2 };
struct GemmP {
  int m_tiles, n_tiles, kblocks;
  int n_off;
  const bf16* res;
  bf16* out;
  int gate_off;
  int m_major;
  int use_flags;
  int n_rot;
  int m_off;
  int signal;
};
__device__ __forceinline__ void tile_coords(const GemmP& p, int t, int& mt, int& nt) {
  if (p.m_major == 2) {
    if (t < 32) { mt = 0; nt = 16 + t; return; }
    const int u = t - 32, b = u / 48, r = u % 48;
    if (b < 15 && r < 32) { mt = b + 1; nt = 16 + r; }
    else { mt = b; nt = b < 15 ? r - 32 : r; }
    return;
  }
  mt = p.m_off + (p.m_major ? t / p.n_tiles : t % p.m_tiles);
  nt = p.m_major ? (t % p.n_tiles + p.n_rot) % p.n_tiles : t / p.m_tiles;
}
template <int BN, int NST, int STGW = 4096, int BM = 128> struct GemmCfg {
  static constexpr int STAGES = NST;
  static constexpr int A_BYTES = BM * 64 * 2, B_BYTES = BN * 64 * 2, STAGE = A_BYTES + B_BYTES;
  static constexpr int STG_OFF = STAGES * STAGE;
  static constexpr int BAR_OFF = STG_OFF + (BM / 16) * STGW;
  static constexpr int SMEM = BAR_OFF + 128;
};
__device__ __forceinline__ float gelu_tanh(float x) {
  float u = 0.7978845608028654f * (x + 0.044715f * x * x * x);
  float t = 1.f - 2.f / (1.f + __expf(2.f * u));
  return 0.5f * x * (1.f + t);
}

template <int BN, int EPI, int NST, int LBT, int LBB, int RC, int BM = 128>
__global__ void __launch_bounds__(LBT, LBB)
gemm_kernel(const __grid_constant__ CUtensorMap tmA, const __grid_constant__ CUtensorMap tmB0,
            const __grid_constant__ CUtensorMap tmB1, const __grid_constant__ CUtensorMap tmB2, GemmP p) {
  constexpr int STGW = EPI == EPI_RES ? 4096 : 2048;
  using C = GemmCfg<BN, NST, STGW, BM>;
  constexpr int NCW = BM / 16;
  extern __shared__ __align__(1024) uint8_t smem_raw[];
  const uint32_t sb = smem_u32(smem_raw);
  if (sb & 1023u) __trap();
  const uint32_t full0 = sb + C::BAR_OFF, empty0 = full0 + 8 * C::STAGES;
  const int warp = threadIdx.x >> 5, lane = threadIdx.x & 31;
  const int tlid = EPI == EPI_QKV ? 2 : (EPI == EPI_GEGLU ? 7 : (p.kblocks == 64 ? 5 : 8));
  TL_START(tlid);
  if (threadIdx.x == 0) {
    for (int i = 0; i < C::STAGES; i++) { mbar_init(full0 + 8 * i, 1); mbar_init(empty0 + 8 * i, NCW); }
    asm volatile("fence.mbarrier_init.release.cluster;" ::: "memory");
    if (p.use_flags) atomicAdd(&g_resident2, 1u);
  }
  __syncthreads();
  const int ntiles = p.m_tiles * p.n_tiles;
  int l_t = blockIdx.x, l_kb = 0, l_st = 0, l_row = 0, l_col = 0; uint32_t l_ph = 1;
  const CUtensorMap* l_mp = &tmB0;
  auto issue_load = [&]() {
    if (l_t >= ntiles) return;
    if (l_kb == 0) {
      int mt, nt; tile_coords(p, l_t, mt, nt);
      if (p.signal) {
        int guard = 0;
        while (ld_acquire32(&g_oflag[mt]) < 128u) { __nanosleep(500); if (++guard > (1 << 21)) { g_err = 7; __trap(); } }
        fence_async_all();
      }
      const int gn = (nt + p.n_off) * BN, mat = gn / HD;
      l_mp = (EPI != EPI_QKV || mat == 0) ? &tmB0 : (mat == 1 ? &tmB1 : &tmB2);
      l_col = EPI == EPI_QKV ? gn % HD : nt * BN;
      l_row = mt * BM;
    }
    mbar_wait(empty0 + 8 * l_st, l_ph);
    const uint32_t fb = full0 + 8 * l_st, sa = sb + l_st * C::STAGE, sbb = sa + C::A_BYTES;
    mbar_expect_tx(fb, C::STAGE);
    tma_load_2d(sa, &tmA, l_kb * 64, l_row, fb);
#pragma unroll
    for (int b = 0; b < BN / 64; b++) tma_load_2d(sbb + b * 8192, l_mp, l_col + b * 64, l_kb * 64, fb);
    if (++l_st == C::STAGES) { l_st = 0; l_ph ^= 1; }
    if (++l_kb == p.kblocks) { l_kb = 0; l_t += gridDim.x; }
  };
  if (RC == 1 && threadIdx.x == 0) {
    for (int i = 0; i < C::STAGES - 1; i++) issue_load();
  }
  if (warp >= NCW) {
    if (RC > 1) asm volatile("setmaxnreg.dec.sync.aligned.u32 24;");
    if (warp == NCW && lane == 0) {
      int st = 0; uint32_t ph = 1;
      for (int t = blockIdx.x; t < ntiles; t += gridDim.x) {
        int mt, nt; tile_coords(p, t, mt, nt);
        if (p.signal) {
          int guard = 0;
          while (ld_acquire32(&g_oflag[mt]) < 128u) { __nanosleep(500); if (++guard > (1 << 21)) { g_err = 7; __trap(); } }
          fence_async_all();
        }
        const int gn = (nt + p.n_off) * BN, mat = gn / HD;
        const CUtensorMap* mp = (EPI != EPI_QKV || mat == 0) ? &tmB0 : (mat == 1 ? &tmB1 : &tmB2);
        const int col = EPI == EPI_QKV ? gn % HD : (EPI == EPI_GEGLU ? nt * (BN / 2) : nt * BN);
        for (int kb = 0; kb < p.kblocks; kb++) {
          mbar_wait(empty0 + 8 * st, ph);
          const uint32_t fb = full0 + 8 * st, sa = sb + st * C::STAGE, sbb = sa + C::A_BYTES;
          mbar_expect_tx(fb, C::STAGE);
          tma_load_2d(sa, &tmA, kb * 64, mt * BM, fb);
          if (EPI == EPI_GEGLU) {
#pragma unroll
            for (int b = 0; b < BN / 128; b++) {
              tma_load_2d(sbb + (2 * b) * 8192, &tmB0, col + b * 64, kb * 64, fb);
              tma_load_2d(sbb + (2 * b + 1) * 8192, &tmB1, col + b * 64, kb * 64, fb);
            }
          } else {
#pragma unroll
            for (int b = 0; b < BN / 64; b++) tma_load_2d(sbb + b * 8192, mp, col + b * 64, kb * 64, fb);
          }
          if (++st == C::STAGES) { st = 0; ph ^= 1; }
        }
      }
    }
    return;
  }
  if (RC > 1) asm volatile("setmaxnreg.inc.sync.aligned.u32 %0;" ::"n"(RC > 1 ? RC : 24));
  const int wg = warp >> 2;
  float acc[BN / 2];
  int st = 0; uint32_t ph = 0;
  const uint32_t stg = sb + C::STG_OFF + warp * STGW;
  for (int t = blockIdx.x; t < ntiles; t += gridDim.x) {
    int mt, nt; tile_coords(p, t, mt, nt);
    int prev = -1;
    for (int kb = 0; kb < p.kblocks; kb++) {
      mbar_wait(full0 + 8 * st, ph);
      const uint32_t sa = sb + st * C::STAGE + wg * 8192, sbb = sb + st * C::STAGE + C::A_BYTES;
      const uint64_t da = (uint64_t)((sa & 0x3FFFF) >> 4) | ((uint64_t)1 << 16) | ((uint64_t)(1024 >> 4) << 32) | ((uint64_t)1 << 62);
      const uint64_t db = (uint64_t)((sbb & 0x3FFFF) >> 4) | ((uint64_t)(8192 >> 4) << 16) | ((uint64_t)(1024 >> 4) << 32) | ((uint64_t)1 << 62);
      wg_fence();
#pragma unroll
      for (int k = 0; k < 4; k++) {
        if (BN == 256) wgmma_n256(acc, da + (uint64_t)(k * 2), db + (uint64_t)(k * 128), (kb | k) != 0);
        else wgmma_n128(acc, da + (uint64_t)(k * 2), db + (uint64_t)(k * 128), (kb | k) != 0);
      }
      wg_commit();
      if (prev >= 0) { wg_wait<1>(); if (lane == 0) mbar_arrive(empty0 + 8 * prev); }
      if (RC == 1) { if (threadIdx.x == 0) issue_load(); __syncwarp(); }
      prev = st;
      if (++st == C::STAGES) { st = 0; ph ^= 1; }
    }
    wg_wait<0>();
    if (lane == 0) mbar_arrive(empty0 + 8 * prev);
    const int row0 = mt * BM + warp * 16;
    const int srow = ((lane >> 3) & 1) * 8 + (lane & 7);
    const int schunk = lane >> 4;
    if (EPI == EPI_QKV) {
      const int gn = (nt + p.n_off) * BN, mat = gn / HD, head0 = (gn % HD) / DH;
      bf16* dstb = mat == 0 ? g_q : (mat == 1 ? g_k : g_v);
#pragma unroll
      for (int hh = 0; hh < BN / 128; hh++) {
#pragma unroll
        for (int hf = 0; hf < 2; hf++) {
          if (lane == 0) bulk_wait_read0();
          __syncwarp();
#pragma unroll
          for (int j = 0; j < 16; j += 4) {
            const float* a = acc + hh * 64 + j * 4 + hf * 2;
            const int r = lane & 7, ch = j + (lane >> 3);
            stsm4(stg + r * 256 + ((ch ^ r) << 4), pack2(a[0], a[1]), pack2(a[4], a[5]), pack2(a[8], a[9]), pack2(a[12], a[13]));
          }
          fence_async_smem();
          __syncwarp();
          if (lane == 0) { bulk_s2g(dstb + ((size_t)(head0 + hh) * S_TOK + row0 + hf * 8) * DH, stg, 2048); bulk_commit(); }
        }
      }
      if (p.use_flags && lane == 0) {
        bulk_wait0();
        fence_async_all();
        red_release_add(&g_kvflag[mt * 96 + nt * (BN / 128)], 1u);
        if (BN == 256) red_release_add(&g_kvflag[mt * 96 + nt * 2 + 1], 1u);
      }
    } else if (EPI == EPI_RES) {
#pragma unroll
      for (int hh = 0; hh < BN / 128; hh++) {
        __syncwarp();
#pragma unroll
        for (int j = 0; j < 16; j += 2) {
          const float* a = acc + hh * 64 + j * 4;
          stsm4(stg + srow * 256 + (((j + schunk) ^ (srow & 7)) << 4), pack2(a[0], a[1]), pack2(a[2], a[3]), pack2(a[4], a[5]), pack2(a[6], a[7]));
        }
        __syncwarp();
        const int ch = lane & 15, col = nt * BN + hh * 128 + ch * 8;
        const float4 g0 = *reinterpret_cast<const float4*>(g_mod + p.gate_off + col);
        const float4 g1 = *reinterpret_cast<const float4*>(g_mod + p.gate_off + col + 4);
#pragma unroll
        for (int i = 0; i < 8; i++) {
          const int r = i * 2 + (lane >> 4);
          uint4 a = lds128(stg + r * 256 + ((ch ^ (r & 7)) << 4));
          uint4 x = *reinterpret_cast<const uint4*>(p.res + (size_t)(row0 + r) * DM + col);
          uint4 o;
          o.x = pack2(lo2f(x.x) + bfr(g0.x * lo2f(a.x)), hi2f(x.x) + bfr(g0.y * hi2f(a.x)));
          o.y = pack2(lo2f(x.y) + bfr(g0.z * lo2f(a.y)), hi2f(x.y) + bfr(g0.w * hi2f(a.y)));
          o.z = pack2(lo2f(x.z) + bfr(g1.x * lo2f(a.z)), hi2f(x.z) + bfr(g1.y * hi2f(a.z)));
          o.w = pack2(lo2f(x.w) + bfr(g1.z * lo2f(a.w)), hi2f(x.w) + bfr(g1.w * hi2f(a.w)));
          *reinterpret_cast<uint4*>(p.out + (size_t)(row0 + r) * DM + col) = o;
        }
      }
    } else {
#pragma unroll
      for (int hh = 0; hh < BN / 128; hh++) {
        __syncwarp();
#pragma unroll
        for (int j = 0; j < 8; j += 2) {
          const float* g = acc + hh * 64 + j * 4;
          const float* u = g + 32;
          float r[8];
#pragma unroll
          for (int e = 0; e < 8; e++) r[e] = bfr(gelu_tanh(bfr(g[e]))) * bfr(u[e]);
          stsm4(stg + srow * 128 + (((j + schunk) ^ (srow & 7)) << 4), pack2(r[0], r[1]), pack2(r[2], r[3]), pack2(r[4], r[5]), pack2(r[6], r[7]));
        }
        __syncwarp();
        const int ch = lane & 7, col = nt * (BN / 2) + hh * 64 + ch * 8;
#pragma unroll
        for (int i = 0; i < 4; i++) {
          const int r = i * 4 + (lane >> 3);
          uint4 a = lds128(stg + r * 128 + ((ch ^ (r & 7)) << 4));
          *reinterpret_cast<uint4*>(g_act + (size_t)(row0 + r) * FF + col) = a;
        }
      }
    }
  }
  if (EPI == EPI_QKV && lane == 0) bulk_wait0();
  TL_END(tlid);
}

__global__ void gate_kernel(unsigned target) {
  for (int i = 0; i < 20000 && ld_acquire32(&g_resident2) < target; i++) __nanosleep(200);
}
#define PROF(i)
#define DELAY_A 700
#define DELAY_B 2000
#define WO_AUX 0
namespace rc {
constexpr int OFF_VW = 0;
constexpr int OFF_WO = OFF_VW + 40960;
constexpr int OFF_K = OFF_WO + 24576;
constexpr int OFF_V = OFF_K + 16384;
constexpr int OFF_RED = OFF_V + 16384;
constexpr int OFF_B = OFF_RED + 16384;
constexpr int OFF_S = OFF_B + 10240;
constexpr int OFF_VM = OFF_S + 3840;
constexpr int OFF_F = OFF_VM + 2048;
constexpr int OFF_O = OFF_F + 2048;
constexpr int OFF_BAR = OFF_O + 2048;
constexpr int OFF_STG = OFF_K;
constexpr int SMEM = OFF_BAR + 128;
constexpr int NCTA = 96;
}
__device__ __forceinline__ float ex2(float x) { float y; asm("ex2.approx.ftz.f32 %0, %1;" : "=f"(y) : "f"(x)); return y; }
__device__ __forceinline__ void bar_arrive(int id, int n) { asm volatile("bar.arrive %0, %1;" ::"r"(id), "r"(n) : "memory"); }

__global__ void __cluster_dims__(3, 1, 1) __launch_bounds__(384, 1)
rec_kernel(const bf16* __restrict__ Wq, const bf16* __restrict__ Wk, const bf16* __restrict__ Wv, const bf16* __restrict__ Wo,
           const bf16* __restrict__ mem0) {
  using namespace rc;
  extern __shared__ __align__(1024) uint8_t smem_raw[];
  const uint32_t sb = smem_u32(smem_raw);
  const int tid = threadIdx.x, warp = tid >> 5, lane = tid & 31;
  const int head = blockIdx.x / 3, rank = blockIdx.x % 3;
  const int rho = lane >> 2, jj = lane & 3;
  const int kap = (lane >> 4) * 8 + (lane & 7);
  const int dhalf = (lane >> 3) & 1;
  const uint32_t bar_kv = sb + OFF_BAR, bar_xs = bar_kv + 16, bar_xv = bar_kv + 24;
  const int wt0 = rank * 13, wnt = rank == 2 ? 14 : 13;
  const int nqk = rank == 2 ? 2 : 3;
  TL_START(3);
  if (tid == 0) {
    atomicAdd(&g_resident, 1u);
    mbar_init(bar_kv, 1); mbar_init(bar_kv + 8, 1); mbar_init(bar_xs, 1); mbar_init(bar_xv, 1);
    asm volatile("fence.mbarrier_init.release.cluster;" ::: "memory");
  }
  asm volatile("barrier.cluster.arrive.aligned;\nbarrier.cluster.wait.aligned;" ::: "memory");

  if (warp < 8) {
    asm volatile("setmaxnreg.inc.sync.aligned.u32 216;");
    const int mg = warp >> 2, kq = warp & 3;
    auto tile_src = [&](int i) -> const bf16* {
      if (rank < 2) {
        if (i < 3) return Wq + head * DH + 48 * rank + 16 * i;
        if (i < 6) return Wk + head * DH + 48 * rank + 16 * (i - 3);
        return Wv + head * DH + 16 * (2 * rank + (i - 6));
      } else {
        if (i < 2) return Wq + head * DH + 96 + 16 * i;
        if (i == 2) return Wv + head * DH + 64;
        if (i < 5) return Wk + head * DH + 96 + 16 * (i - 3);
        if (i == 5) return Wv + head * DH + 80;
        return Wv + head * DH + 96 + 16 * (i - 6);
      }
    };
    const int kcol0 = 16 * ((kap & 7) >> 2) + 4 * (((kap & 7) >> 1) & 1) + (kap >> 3) + 8 * (kap & 1);
    uint32_t wa[3][10][4];
    uint32_t wo[8][4];
    const uint32_t lrow = sb + OFF_STG + (kq * 160 + kcol0) * 32 + dhalf * 16;
#pragma unroll
    for (int pass = 0; pass < 3; pass++) {
      const int nt = pass < 2 ? 3 : 2;
      for (int ti = 0; ti < nt; ti++) {
        const bf16* src = tile_src(pass * 3 + ti);
        for (int e = tid; e < 1280; e += 256) {
          const int r = e >> 1, hf = e & 1;
          cp_async16(sb + OFF_STG + ti * 20480 + r * 32 + hf * 16, src + (size_t)r * HD + hf * 8);
        }
      }
      cp_async_wait_all();
      bar_sync(9, 256);
      if (pass < 2) {
        if (mg == pass) {
#pragma unroll
          for (int ti = 0; ti < 3; ti++)
#pragma unroll
            for (int ks = 0; ks < 10; ks++) ldsm4t(wa[ti][ks], lrow + ti * 20480 + ((ks >> 1) * 32 + (ks & 1) * 2) * 32);
        }
      } else {
#pragma unroll
        for (int ks = 0; ks < 10; ks++) {
          uint32_t r[4];
          ldsm4t(r, lrow + mg * 20480 + ((ks >> 1) * 32 + (ks & 1) * 2) * 32);
          sts128(sb + OFF_VW + (mg * 40 + kq * 10 + ks) * 512 + lane * 16, r[0], r[1], r[2], r[3]);
        }
      }
      bar_sync(9, 256);
    }
    {
      const int cpr = wnt * 2;
      for (int e = tid; e < 128 * cpr; e += 256) {
        const int r = e / cpr, c = e % cpr;
        cp_async16(sb + OFF_STG + r * 464 + c * 16, Wo + (size_t)(head * DH + r) * DM + wt0 * 16 + c * 8);
      }
      cp_async_wait_all();
      bar_sync(9, 256);
#pragma unroll
      for (int ks = 0; ks < 8; ks++) ldsm4t(wo[ks], sb + OFF_STG + (ks * 16 + kap) * 464 + warp * 32 + dhalf * 16);
      for (int t = 8; t < wnt; t++) {
        uint32_t r[4];
        ldsm4t(r, sb + OFF_STG + (warp * 16 + kap) * 464 + t * 32 + dhalf * 16);
        sts128(sb + OFF_WO + ((t - 8) * 8 + warp) * 512 + lane * 16, r[0], r[1], r[2], r[3]);
      }
    }
    fence_async_smem();
    bar_sync(10, 384);
    uint32_t t_pub = (uint32_t)clock() - DELAY_B;
    const uint32_t vb = sb + OFF_VW + (mg * 40 + kq * 10) * 512 + lane * 16;
    float* const part_dst = g_part + ((((size_t)(wt0 + warp) * 4 + jj) * 32 + head) * 8 + rho) * 4;
    const bool two = !WO_AUX && warp < wnt - 8;
    const int ttype = rank < 2 ? (warp < 3 ? 0 : (warp < 6 ? 1 : 2)) : ((warp == 2 || warp >= 5) ? 2 : (warp < 2 ? 0 : 1));
    const int vt = rank < 2 ? 2 * rank + (warp - 6) : (warp == 2 ? 4 : (warp == 5 ? 5 : warp));

    for (int s = 0; s < NSEG; s++) {
      const uint32_t par = s & 1;
      const bool last = s == NSEG - 1;
      PROF(0);
      const uint4 va0 = lds128(vb);
      {
        const uint4* src = reinterpret_cast<const uint4*>(g_memb) + (s & 3) * 640 + (kq * 5 + mg * 3) * 32 + lane;
        while ((int)((uint32_t)clock() - t_pub) < DELAY_B) { }
        uint4 x0, x1, x2 = make_uint4(0, 0, 0, 0);
        int guard = 0;
        while (true) {
          x0 = ldg_relaxed128(src); x1 = ldg_relaxed128(src + 32);
          if (mg == 0) x2 = ldg_relaxed128(src + 64);
          const bool ok = x0.x != ~0u && x0.y != ~0u && x0.z != ~0u && x0.w != ~0u && x1.x != ~0u && x1.y != ~0u && x1.z != ~0u && x1.w != ~0u &&
                          x2.x != ~0u && x2.y != ~0u && x2.z != ~0u && x2.w != ~0u;
          if (__all_sync(~0u, ok)) break;
          if (++guard > (1 << 22)) { g_err = 3; __trap(); }
        }
        const uint32_t bb = sb + OFF_B + (kq * 5 + mg * 3) * 512 + lane * 16;
        sts128(bb, x0.x, x0.y, x0.z, x0.w); sts128(bb + 512, x1.x, x1.y, x1.z, x1.w);
        if (mg == 0) sts128(bb + 1024, x2.x, x2.y, x2.z, x2.w);
        bar_sync(1 + kq, 64);
      }
      PROF(1);
      {
        float c[4][4];
#pragma unroll
        for (int ti = 0; ti < 4; ti++) c[ti][0] = c[ti][1] = c[ti][2] = c[ti][3] = 0.f;
        const uint32_t bb = sb + OFF_B + kq * 2560 + lane * 16;
        uint4 bf[5];
#pragma unroll
        for (int kk = 0; kk < 5; kk++) bf[kk] = lds128(bb + kk * 512);
        uint4 an = va0;
#pragma unroll
        for (int ks = 0; ks < 10; ks++) {
          const uint32_t b0 = (ks & 1) ? bf[ks >> 1].z : bf[ks >> 1].x, b1 = (ks & 1) ? bf[ks >> 1].w : bf[ks >> 1].y;
          const uint4 a0 = an;
          if (ks < 9) an = lds128(vb + (ks + 1) * 512);
#pragma unroll
          for (int ti = 0; ti < 3; ti++) mma16816(c[ti], wa[ti][ks][0], wa[ti][ks][1], wa[ti][ks][2], wa[ti][ks][3], b0, b1);
          mma16816(c[3], a0.x, a0.y, a0.z, a0.w, b0, b1);
        }
#pragma unroll
        for (int ti = 0; ti < 3; ti++) sts128f(sb + OFF_RED + ((mg * 3 + ti) * 4 + kq) * 512 + lane * 16, c[ti]);
        sts128f(sb + OFF_RED + ((6 + mg) * 4 + kq) * 512 + lane * 16, c[3]);
      }
      PROF(2);
      bar_sync(5, 256);
      {
        const uint32_t ra = sb + OFF_RED + warp * 2048 + lane * 16;
        float4 q0 = lds128f(ra), q1 = lds128f(ra + 512), q2 = lds128f(ra + 1024), q3 = lds128f(ra + 1536);
        const uint32_t a0 = pack2((q0.x + q1.x) + (q2.x + q3.x), (q0.y + q1.y) + (q2.y + q3.y));
        const uint32_t a1 = pack2((q0.z + q1.z) + (q2.z + q3.z), (q0.w + q1.w) + (q2.w + q3.w));
        if (ttype == 2 && !last) {
#pragma unroll
          for (int r = 0; r < 3; r++) st_async64(mapa(sb + OFF_VM + vt * 256 + lane * 8, r), a0, a1, mapa(bar_xv, r));
        }
        const uint32_t f0 = movtrans(a0), f1 = movtrans(a1);
        if (ttype < 2) sts64(sb + OFF_F + warp * 256 + lane * 8, f0, f1);
        bar_arrive(6, 384);
        PROF(3);
        if (ttype) {
          const int c0 = ttype == 1 ? rank * 6 + 2 * (warp - 3) : 2 * vt;
          uint32_t* dst = reinterpret_cast<uint32_t*>((ttype == 1 ? g_km : g_vm) + ((size_t)(s * NH + head) * NMEM + rho) * DH);
          dst[((c0 ^ rho) << 2) + jj] = f0;
          dst[(((c0 + 1) ^ rho) << 2) + jj] = f1;
        }
      }
      if (last) break;
      uint4 pf[8];
      if (two) {
#pragma unroll
        for (int ks = 0; ks < 8; ks++) pf[ks] = lds128(sb + OFF_WO + (warp * 8 + ks) * 512 + lane * 16);
      }
      PROF(8);
      bar_sync(8, 384);
      const uint32_t flag = ((s >> 1) & 1) ^ 1;
      {
        float c[4][4];
#pragma unroll
        for (int a = 0; a < 4; a++) c[a][0] = c[a][1] = c[a][2] = c[a][3] = 0.f;
#pragma unroll
        for (int h = 0; h < 2; h++) {
          const uint4 o0 = lds128(sb + OFF_O + (2 * h) * 512 + lane * 16), o1 = lds128(sb + OFF_O + (2 * h + 1) * 512 + lane * 16);
          mma16816(c[0], wo[4 * h][0], wo[4 * h][1], wo[4 * h][2], wo[4 * h][3], o0.x, o0.y);
          mma16816(c[1], wo[4 * h + 1][0], wo[4 * h + 1][1], wo[4 * h + 1][2], wo[4 * h + 1][3], o0.z, o0.w);
          if (two) {
            mma16816(c[2], pf[4 * h].x, pf[4 * h].y, pf[4 * h].z, pf[4 * h].w, o0.x, o0.y);
            mma16816(c[3], pf[4 * h + 1].x, pf[4 * h + 1].y, pf[4 * h + 1].z, pf[4 * h + 1].w, o0.z, o0.w);
          }
          mma16816(c[0], wo[4 * h + 2][0], wo[4 * h + 2][1], wo[4 * h + 2][2], wo[4 * h + 2][3], o1.x, o1.y);
          mma16816(c[1], wo[4 * h + 3][0], wo[4 * h + 3][1], wo[4 * h + 3][2], wo[4 * h + 3][3], o1.z, o1.w);
          if (two) {
            mma16816(c[2], pf[4 * h + 2].x, pf[4 * h + 2].y, pf[4 * h + 2].z, pf[4 * h + 2].w, o1.x, o1.y);
            mma16816(c[3], pf[4 * h + 3].x, pf[4 * h + 3].y, pf[4 * h + 3].z, pf[4 * h + 3].w, o1.z, o1.w);
          }
        }
        float* dst0 = part_dst + (size_t)par * (160 * 32 * 8 * 4);
#pragma unroll
        for (int a = 0; a < 2; a++) {
          if (a == 0 || two) {
            uint32_t w[4];
#pragma unroll
            for (int e = 0; e < 4; e++) w[e] = (__float_as_uint(c[2 * a][e] + c[2 * a + 1][e]) & ~1u) | flag;
            stg_relaxed128(dst0 + a * (8 * 4 * 32 * 8 * 4), w[0], w[1], w[2], w[3]);
          }
        }
      }
      t_pub = (uint32_t)clock();
      PROF(9);
    }
  } else {
    asm volatile("setmaxnreg.dec.sync.aligned.u32 72;");
    const int aw = warp - 8;
    const bf16* kbase = g_k + (size_t)head * S_TOK * DH;
    const bf16* vbase = g_v + (size_t)head * S_TOK * DH;
    {
      const int gt = blockIdx.x * 128 + (tid - 256), GT = NCTA * 128;
      uint4* pp = reinterpret_cast<uint4*>(g_part);
      for (int i = gt; i < 2 * 160 * 32 * 8; i += GT) pp[i] = make_uint4(0, 0, 0, 0);
      uint4* pm = reinterpret_cast<uint4*>(g_memb);
      for (int i = gt + 640; i < 4 * 640; i += GT) pm[i] = make_uint4(~0u, ~0u, ~0u, ~0u);
      if (gt < 2560) {
        const int i = gt & 3, l = (gt >> 2) & 31, kk = gt >> 7;
        const int n = l >> 2, u = 4 * kk + (l & 3), col = 16 * (u >> 1) + 4 * (u & 1) + i;
        const uint32_t lo = reinterpret_cast<const unsigned short*>(mem0)[n * DM + col];
        const uint32_t hi = reinterpret_cast<const unsigned short*>(mem0)[n * DM + col + 8];
        uint32_t wv = lo | (hi << 16);
        if (wv == 0xffffffffu) wv = 0x7fff7fffu;
        g_memb[gt] = wv;
      }
      __threadfence();
      bar_sync(11, 128);
      if (aw == 0 && lane == 0) {
        atomicAdd(&g_ready, 1u);
        int guard = 0;
        while (ld_acquire32(&g_ready) < (unsigned)NCTA) { __nanosleep(200); if (++guard > (1 << 22)) { g_err = 8; __trap(); } }
      }
    }
    auto load_kv = [&](int sg) {
      if ((sg & 3) == 0) {
        const unsigned* f = g_kvflag + (sg >> 2) * 96 + 32 + head;
        int guard = 0;
        while (ld_acquire32(f) < 8u || ld_acquire32(f + 32) < 8u) { __nanosleep(100); if (++guard > (1 << 22)) { g_err = 5; __trap(); } }
        fence_async_all();
      }
      const int b = sg & 1;
      mbar_expect_tx(bar_kv + 8 * b, 16384);
      bulk_g2s(sb + OFF_K + b * 8192, kbase + (size_t)sg * SEG * DH, 8192, bar_kv + 8 * b);
      bulk_g2s(sb + OFF_V + b * 8192, vbase + (size_t)sg * SEG * DH, 8192, bar_kv + 8 * b);
    };
    bar_sync(10, 384);
    if (aw == 1 && lane == 0) { load_kv(0); load_kv(1); }
    __syncwarp();
    const int unit = (3 - aw) * NCTA + blockIdx.x;
    const bool is_red = unit < 160;
    for (int s = 0; s < NSEG - 1; s++) {
      const uint32_t par = s & 1;
      if (aw == 0 && lane == 0) { mbar_expect_tx(bar_xs, 3840); mbar_expect_tx(bar_xv, 2048); }
      PROF(0);
      uint32_t kf[3][2], va[2][2][4];
      mbar_wait(bar_kv + 8 * par, (s >> 1) & 1);
      {
        const int key = aw * 8 + (lane & 7);
#pragma unroll
        for (int i = 0; i < 3; i++) {
          const int ch = rank * 6 + 2 * i + dhalf;
          if (i < nqk) ldsm2(kf[i], sb + OFF_K + par * 8192 + key * 256 + ((ch ^ (key & 7)) << 4));
          else kf[i][0] = kf[i][1] = 0u;
        }
#pragma unroll
        for (int m = 0; m < 2; m++)
#pragma unroll
          for (int ks = 0; ks < 2; ks++) {
            const int k2 = ks * 16 + kap, ch = 2 * (aw + 4 * m) + dhalf;
            ldsm4t(va[m][ks], sb + OFF_V + par * 8192 + k2 * 256 + ((ch ^ (k2 & 7)) << 4));
          }
      }
      PROF(1);
      bar_sync(6, 384);
      {
        float sc[2][4], sm[2][4];
        uint2 qa[3], kk[3];
#pragma unroll
        for (int i = 0; i < 3; i++) {
          qa[i] = make_uint2(0u, 0u); kk[i] = make_uint2(0u, 0u);
          if (i < nqk) qa[i] = lds64(sb + OFF_F + i * 256 + lane * 8);
        }
        if (aw == 3) {
#pragma unroll
          for (int i = 0; i < 3; i++) if (i < nqk) kk[i] = lds64(sb + OFF_F + (3 + i) * 256 + lane * 8);
        }
#pragma unroll
        for (int i = 0; i < 2; i++) { sc[i][0] = sc[i][1] = sc[i][2] = sc[i][3] = 0.f; sm[i][0] = sm[i][1] = sm[i][2] = sm[i][3] = 0.f; }
#pragma unroll
        for (int i = 0; i < 3; i++) mma16816(sc[i & 1], qa[i].x, 0u, qa[i].y, 0u, kf[i][0], kf[i][1]);
        if (aw == 3) {
#pragma unroll
          for (int i = 0; i < 3; i++) mma16816(sm[i & 1], qa[i].x, 0u, qa[i].y, 0u, kk[i].x, kk[i].y);
        }
        const uint32_t dl = sb + OFF_S + rank * 1280 + lane * 8;
        const uint32_t s0 = __float_as_uint(sc[0][0] + sc[1][0]), s1 = __float_as_uint(sc[0][1] + sc[1][1]);
#pragma unroll
        for (int r = 0; r < 3; r++) st_async64(mapa(dl + aw * 256, r), s0, s1, mapa(bar_xs, r));
        if (aw == 3) {
          const uint32_t m0 = __float_as_uint(sm[0][0] + sm[1][0]), m1 = __float_as_uint(sm[0][1] + sm[1][1]);
#pragma unroll
          for (int r = 0; r < 3; r++) st_async64(mapa(dl + 1024, r), m0, m1, mapa(bar_xs, r));
        }
      }
      PROF(4);
      mbar_wait(bar_xs, par);
      PROF(6);
      float v[10];
      {
        const uint32_t sa = sb + OFF_S + lane * 8;
#pragma unroll
        for (int n = 0; n < 5; n++) {
          const uint2 a = lds64(sa + n * 256), b = lds64(sa + 1280 + n * 256), c = lds64(sa + 2560 + n * 256);
          v[2 * n] = __uint_as_float(a.x) + __uint_as_float(b.x) + __uint_as_float(c.x);
          v[2 * n + 1] = __uint_as_float(a.y) + __uint_as_float(b.y) + __uint_as_float(c.y);
        }
      }
      float mx = fmaxf(fmaxf(fmaxf(v[0], v[1]), fmaxf(v[2], v[3])), fmaxf(fmaxf(v[4], v[5]), fmaxf(v[6], v[7])));
      mx = fmaxf(mx, fmaxf(v[8], v[9]));
      mx = fmaxf(mx, __shfl_xor_sync(~0u, mx, 1));
      mx = fmaxf(mx, __shfl_xor_sync(~0u, mx, 2));
      const float kscale = 0.08838834764831845f * 1.4426950408889634f;
      const float mo = -mx * kscale;
#pragma unroll
      for (int i = 0; i < 10; i++) v[i] = ex2(fmaf(v[i], kscale, mo));
      const uint32_t p0 = pack2(v[0], v[1]), p1 = pack2(v[2], v[3]), p2 = pack2(v[4], v[5]), p3 = pack2(v[6], v[7]), p4 = pack2(v[8], v[9]);
      PROF(7);
      {
        float c[2][4], d[2][4];
#pragma unroll
        for (int m = 0; m < 2; m++) {
          c[m][0] = c[m][1] = c[m][2] = c[m][3] = 0.f; d[m][0] = d[m][1] = d[m][2] = d[m][3] = 0.f;
          mma16816(c[m], va[m][0][0], va[m][0][1], va[m][0][2], va[m][0][3], p0, p1);
          mma16816(d[m], va[m][1][0], va[m][1][1], va[m][1][2], va[m][1][3], p2, p3);
        }
        mbar_wait(bar_xv, par);
        uint2 vm[2];
#pragma unroll
        for (int m = 0; m < 2; m++) vm[m] = lds64(sb + OFF_VM + (aw + 4 * m) * 256 + lane * 8);
#pragma unroll
        for (int m = 0; m < 2; m++) mma16816(d[m], vm[m].x, vm[m].y, 0u, 0u, p4, 0u);
        float sum = ((lo2f(p0) + hi2f(p0)) + (lo2f(p1) + hi2f(p1))) + ((lo2f(p2) + hi2f(p2)) + (lo2f(p3) + hi2f(p3))) + (lo2f(p4) + hi2f(p4));
        sum += __shfl_xor_sync(~0u, sum, 1);
        sum += __shfl_xor_sync(~0u, sum, 2);
        const float inv = __fdividef(1.f, sum);
        const float i0 = __shfl_sync(~0u, inv, jj * 8), i1 = __shfl_sync(~0u, inv, jj * 8 + 4);
#pragma unroll
        for (int m = 0; m < 2; m++) {
          const int mt = aw + 4 * m;
          const uint32_t b0 = movtrans(pack2((c[m][0] + d[m][0]) * i0, (c[m][1] + d[m][1]) * i1));
          const uint32_t b1 = movtrans(pack2((c[m][2] + d[m][2]) * i0, (c[m][3] + d[m][3]) * i1));
          sts64(sb + OFF_O + (mt >> 1) * 512 + lane * 16 + (mt & 1) * 8, b0, b1);
        }
      }
      PROF(8);
      bar_sync(8, 384);
      const uint32_t flag = ((s >> 1) & 1) ^ 1;
      const uint32_t t_o = (uint32_t)clock();
      PROF(9);
      if (aw == 1 && lane == 0) {
        __threadfence();
        atomicAdd(&g_mflag[s * NH + head], 1u);
        if (s + 2 < NSEG - 1) load_kv(s + 2);
      }
      if (is_red) {
        const uint4* src = reinterpret_cast<const uint4*>(g_part) + ((size_t)par * 160 + unit) * 256 + lane;
        uint4 w[8];
        int guard = 0;
        while ((int)((uint32_t)clock() - t_o) < DELAY_A + (WO_AUX ? 0 : 300)) { }
        while (true) {
#pragma unroll
          for (int i = 0; i < 8; i++) w[i] = ldg_relaxed128(src + i * 32);
          uint32_t a = ~0u, o = 0u;
#pragma unroll
          for (int i = 0; i < 8; i++) { a &= w[i].x & w[i].y & w[i].z & w[i].w; o |= w[i].x | w[i].y | w[i].z | w[i].w; }
          const bool ok = flag ? (a & 1u) : !(o & 1u);
          if (__all_sync(~0u, ok)) break;
          if (++guard > (1 << 22)) { g_err = 4; __trap(); }
        }
        PROF(10);
#define F_(i, m) __uint_as_float(w[i].m)
        float r0 = ((F_(0, x) + F_(1, x)) + (F_(2, x) + F_(3, x))) + ((F_(4, x) + F_(5, x)) + (F_(6, x) + F_(7, x)));
        float r1 = ((F_(0, y) + F_(1, y)) + (F_(2, y) + F_(3, y))) + ((F_(4, y) + F_(5, y)) + (F_(6, y) + F_(7, y)));
        float r2 = ((F_(0, z) + F_(1, z)) + (F_(2, z) + F_(3, z))) + ((F_(4, z) + F_(5, z)) + (F_(6, z) + F_(7, z)));
        float r3 = ((F_(0, w) + F_(1, w)) + (F_(2, w) + F_(3, w))) + ((F_(4, w) + F_(5, w)) + (F_(6, w) + F_(7, w)));
#undef F_
#pragma unroll
        for (int o = 8; o < 32; o <<= 1) {
          r0 += __shfl_xor_sync(~0u, r0, o); r1 += __shfl_xor_sync(~0u, r1, o);
          r2 += __shfl_xor_sync(~0u, r2, o); r3 += __shfl_xor_sync(~0u, r3, o);
        }
        if (lane < 16) {
          const int t = unit >> 2, j = unit & 3, e = lane >> 3, r8 = lane & 7;
          const int w0 = ((t >> 1) * 32 + (2 * j + e) * 4 + (t & 1) * 2) * 4 + r8;
          stg_relaxed32(g_memb + ((s + 1) & 3) * 2560 + w0, e ? pack2(r1, r3) : pack2(r0, r2));
          stg_relaxed32(g_memb + ((s + 3) & 3) * 2560 + w0, ~0u);
        }
      }
    }
    bar_sync(6, 384);
  }
  asm volatile("barrier.cluster.arrive;\nbarrier.cluster.wait;" ::: "memory");
  if (tid == 0) { __threadfence(); atomicAdd(&g_mflag[(NSEG - 1) * NH + head], 1u); }
  TL_END(3);
}

#define ATT_SLEEP 400
constexpr int ATT_BUF = 8192 * 3 + 4096;
constexpr int ATT_SMEM = 2 * ATT_BUF + 64;
__global__ void __launch_bounds__(128) attn_kernel() {
  extern __shared__ __align__(1024) uint8_t smem_raw[];
  const int warp = threadIdx.x >> 5, lane = threadIdx.x & 31;
  const int pr = warp >> 1, wp = warp & 1;
  const uint32_t sb = smem_u32(smem_raw) + pr * ATT_BUF;
  const uint32_t sQ = sb, sK = sb + 8192, sV = sb + 16384, sKm = sb + 24576, sVm = sKm + 2048;
  const uint32_t bar = smem_u32(smem_raw) + 2 * ATT_BUF + pr * 8;
  const int head = blockIdx.x & 31;
  TL_START(4);
  if (threadIdx.x == 0) {
    mbar_init(bar, 2); mbar_init(bar + 8, 2);
    asm volatile("fence.mbarrier_init.release.cluster;" ::: "memory");
  }
  __syncthreads();
  for (int seg = (blockIdx.x >> 5) * 2 + pr, it = 0; it < 1; it++) {
  if (wp == 0) {
    if (lane < 3) {
      const unsigned* fq = g_kvflag + (seg >> 2) * 96 + head + lane * 32;
      int guard = 0;
      while (ld_acquire32(fq) < 8u) { __nanosleep(1000); if (++guard > (1 << 21)) { g_err = 6; __trap(); } }
    }
    __syncwarp();
    if (lane == 0) {
      fence_async_all();
      mbar_expect_tx(bar, 8192 * 3);
      const size_t off = ((size_t)head * S_TOK + seg * SEG) * DH;
      bulk_g2s(sQ, g_q + off, 8192, bar); bulk_g2s(sK, g_k + off, 8192, bar); bulk_g2s(sV, g_v + off, 8192, bar);
    }
  } else if (lane == 0) {
    const unsigned* fm = g_mflag + seg * NH + head;
    int guard = 0;
    while (ld_acquire32(fm) < 3u) { __nanosleep(ATT_SLEEP); if (++guard > (1 << 22)) { g_err = 6; __trap(); } }
    fence_async_all();
    mbar_expect_tx(bar, 4096);
    const size_t offm = (size_t)(seg * NH + head) * NMEM * DH;
    bulk_g2s(sKm, g_km + offm, 2048, bar); bulk_g2s(sVm, g_vm + offm, 2048, bar);
  }
  __syncwarp();
  mbar_wait(bar, it & 1);
  const int rho = lane >> 2, jj = lane & 3;
  float sc[5][4];
#pragma unroll
  for (int n = 0; n < 5; n++) sc[n][0] = sc[n][1] = sc[n][2] = sc[n][3] = 0.f;
#pragma unroll
  for (int ks = 0; ks < 8; ks++) {
    uint32_t a[4];
    {
      const int row = wp * 16 + ((lane >> 3) & 1) * 8 + (lane & 7), ch = 2 * ks + (lane >> 4);
      ldsm4(a, sQ + row * 256 + ((ch ^ (row & 7)) << 4));
    }
#pragma unroll
    for (int n = 0; n < 4; n += 2) {
      uint32_t kf[4];
      const int key = (n + (lane >> 4)) * 8 + (lane & 7), ch = 2 * ks + ((lane >> 3) & 1);
      ldsm4(kf, sK + key * 256 + ((ch ^ (key & 7)) << 4));
      mma16816(sc[n], a[0], a[1], a[2], a[3], kf[0], kf[1]);
      mma16816(sc[n + 1], a[0], a[1], a[2], a[3], kf[2], kf[3]);
    }
    uint32_t mf[2];
    {
      const int key = lane & 7, ch = 2 * ks + ((lane >> 3) & 1);
      ldsm2(mf, sKm + key * 256 + ((ch ^ key) << 4));
    }
    mma16816(sc[4], a[0], a[1], a[2], a[3], mf[0], mf[1]);
  }
  uint32_t pa[3][4];
  {
    float mx0 = -3.0e38f, mx1 = -3.0e38f;
    const int q0 = wp * 16 + rho, q1 = q0 + 8;
#pragma unroll
    for (int n = 0; n < 5; n++) {
#pragma unroll
      for (int e = 0; e < 4; e++) {
        float v = bfr(bfr(sc[n][e]) * 0.08838834764831845f);
        if (n < 4) { const int key = n * 8 + jj * 2 + (e & 1); if (key > ((e & 2) ? q1 : q0)) v = -1.0e9f; }
        sc[n][e] = v;
        if (e & 2) mx1 = fmaxf(mx1, v); else mx0 = fmaxf(mx0, v);
      }
    }
    mx0 = fmaxf(mx0, __shfl_xor_sync(~0u, mx0, 1)); mx0 = fmaxf(mx0, __shfl_xor_sync(~0u, mx0, 2));
    mx1 = fmaxf(mx1, __shfl_xor_sync(~0u, mx1, 1)); mx1 = fmaxf(mx1, __shfl_xor_sync(~0u, mx1, 2));
    float s0 = 0.f, s1 = 0.f;
#pragma unroll
    for (int n = 0; n < 5; n++) {
      sc[n][0] = __expf(sc[n][0] - mx0); sc[n][1] = __expf(sc[n][1] - mx0); s0 += sc[n][0] + sc[n][1];
      sc[n][2] = __expf(sc[n][2] - mx1); sc[n][3] = __expf(sc[n][3] - mx1); s1 += sc[n][2] + sc[n][3];
    }
    s0 += __shfl_xor_sync(~0u, s0, 1); s0 += __shfl_xor_sync(~0u, s0, 2);
    s1 += __shfl_xor_sync(~0u, s1, 1); s1 += __shfl_xor_sync(~0u, s1, 2);
    const float i0 = 1.f / s0, i1 = 1.f / s1;
#pragma unroll
    for (int ks = 0; ks < 2; ks++) {
      pa[ks][0] = pack2(sc[2 * ks][0] * i0, sc[2 * ks][1] * i0); pa[ks][1] = pack2(sc[2 * ks][2] * i1, sc[2 * ks][3] * i1);
      pa[ks][2] = pack2(sc[2 * ks + 1][0] * i0, sc[2 * ks + 1][1] * i0); pa[ks][3] = pack2(sc[2 * ks + 1][2] * i1, sc[2 * ks + 1][3] * i1);
    }
    pa[2][0] = pack2(sc[4][0] * i0, sc[4][1] * i0); pa[2][1] = pack2(sc[4][2] * i1, sc[4][3] * i1); pa[2][2] = 0; pa[2][3] = 0;
  }
  __syncwarp();
  const int srow = ((lane >> 3) & 1) * 8 + (lane & 7), schunk = lane >> 4;
#pragma unroll
  for (int n = 0; n < 16; n += 2) {
    float o0[4] = {0.f, 0.f, 0.f, 0.f}, o1[4] = {0.f, 0.f, 0.f, 0.f};
#pragma unroll
    for (int ks = 0; ks < 2; ks++) {
      uint32_t vf[4];
      const int key = ks * 16 + ((lane >> 3) & 1) * 8 + (lane & 7), ch = n + (lane >> 4);
      ldsm4t(vf, sV + key * 256 + ((ch ^ (key & 7)) << 4));
      mma16816(o0, pa[ks][0], pa[ks][1], pa[ks][2], pa[ks][3], vf[0], vf[1]);
      mma16816(o1, pa[ks][0], pa[ks][1], pa[ks][2], pa[ks][3], vf[2], vf[3]);
    }
    uint32_t mf[2];
    {
      const int key = lane & 7, ch = n + ((lane >> 3) & 1);
      ldsm2t(mf, sVm + key * 256 + ((ch ^ key) << 4));
    }
    mma16816(o0, pa[2][0], pa[2][1], 0u, 0u, mf[0], 0u);
    mma16816(o1, pa[2][0], pa[2][1], 0u, 0u, mf[1], 0u);
    stsm4(sQ + (wp * 16 + srow) * 256 + (((n + schunk) ^ (srow & 7)) << 4), pack2(o0[0], o0[1]), pack2(o0[2], o0[3]), pack2(o1[0], o1[1]), pack2(o1[2], o1[3]));
  }
  __syncwarp();
#pragma unroll
  for (int i = 0; i < 8; i++) {
    const int r = i * 2 + (lane >> 4), ch = lane & 15;
    uint4 a = lds128(sQ + (wp * 16 + r) * 256 + ((ch ^ (r & 7)) << 4));
    *reinterpret_cast<uint4*>(g_o + (size_t)(seg * SEG + wp * 16 + r) * HD + head * DH + ch * 8) = a;
  }
  }
  TL_END(4);
}

typedef CUresult (*EncodeFn)(CUtensorMap*, CUtensorMapDataType, cuuint32_t, void*, const cuuint64_t*, const cuuint64_t*,
                             const cuuint32_t*, const cuuint32_t*, CUtensorMapInterleave, CUtensorMapSwizzle,
                             CUtensorMapL2promotion, CUtensorMapFloatOOBfill);
#define QKV_ST 3
#define GK_QKV gemm_kernel<256, EPI_QKV, QKV_ST, 288, 1, 0>
#define GK_RES gemm_kernel<128, EPI_RES, 4, 640, 1, 128>
#define GK_RESB gemm_kernel<128, EPI_RES, 5, 288, 1, 0>
constexpr int SM_RESB = GemmCfg<128, 5>::SMEM;
#define GK_RES64 gemm_kernel<128, EPI_RES, 4, 160, 2, 0, 64>
constexpr int SM_RES64 = GemmCfg<128, 4, 4096, 64>::SMEM;
#define ATT_LSMEM ATT_SMEM
#define EARLY 0
#define WO64 0
#define WO_SPLIT 12
#define GK_GLU gemm_kernel<128, EPI_GEGLU, 3, 288, 2, 0>
constexpr int SM_QKV = GemmCfg<256, QKV_ST, 2048>::SMEM, SM_RES = GemmCfg<128, 4>::SMEM, SM_GLU = GemmCfg<128, 3, 2048>::SMEM;
static EncodeFn s_encode = nullptr;
static cudaStream_t s_rec, s_att;
static cudaEvent_t s_evFork, s_evJoin, s_evFork2, s_evJoin2, s_evJoin3;
#define SHADOW_CTAS 36

static CUtensorMap make_map(const void* ptr, uint64_t inner, uint64_t outer, uint32_t box_inner, uint32_t box_outer, bool swz = true) {
  CUtensorMap m;
  cuuint64_t dims[2] = {inner, outer};
  cuuint64_t strides[1] = {inner * 2};
  cuuint32_t box[2] = {box_inner, box_outer};
  cuuint32_t es[2] = {1, 1};
  s_encode(&m, CU_TENSOR_MAP_DATA_TYPE_BFLOAT16, 2, const_cast<void*>(ptr), dims, strides, box, es, CU_TENSOR_MAP_INTERLEAVE_NONE,
           swz ? CU_TENSOR_MAP_SWIZZLE_128B : CU_TENSOR_MAP_SWIZZLE_NONE, CU_TENSOR_MAP_L2_PROMOTION_L2_256B, CU_TENSOR_MAP_FLOAT_OOB_FILL_NONE);
  return m;
}
template <class T> static void* sym_addr(T& sym) { void* p = nullptr; cudaGetSymbolAddress(&p, sym); return p; }

extern "C" void kernel_launch(void* const* d_in, const int* in_sizes, int n_in, void* d_out, int out_size) {
  const bf16* x = (const bf16*)d_in[0];
  const bf16* mem0 = (const bf16*)d_in[1];
  const bf16* Wq = (const bf16*)d_in[2];
  const bf16* Wk = (const bf16*)d_in[3];
  const bf16* Wv = (const bf16*)d_in[4];
  const bf16* Wo = (const bf16*)d_in[5];
  const bf16* w_gate = (const bf16*)d_in[8];
  const bf16* w_up = (const bf16*)d_in[9];
  const bf16* w_down = (const bf16*)d_in[10];
  const bf16* cvec = (const bf16*)d_in[11];
  const bf16* w_mod = (const bf16*)d_in[12];
  bf16* out = (bf16*)d_out;

  static bool init = false;
  static void *p_h, *p_o, *p_x1, *p_h2, *p_act, *p_k;
  if (!init) {
    cudaDriverEntryPointQueryResult qr;
    void* fn = nullptr;
    cudaGetDriverEntryPoint("cuTensorMapEncodeTiled", &fn, cudaEnableDefault, &qr);
    s_encode = (EncodeFn)fn;
    p_h = sym_addr(g_h); p_o = sym_addr(g_o); p_x1 = sym_addr(g_x1); p_h2 = sym_addr(g_h2); p_act = sym_addr(g_act); p_k = sym_addr(g_k);
    cudaFuncSetAttribute(GK_QKV, cudaFuncAttributeMaxDynamicSharedMemorySize, SM_QKV);
    cudaFuncSetAttribute(GK_RES, cudaFuncAttributeMaxDynamicSharedMemorySize, SM_RES);
    cudaFuncSetAttribute(GK_RES64, cudaFuncAttributeMaxDynamicSharedMemorySize, SM_RES64);
    cudaFuncSetAttribute(GK_RESB, cudaFuncAttributeMaxDynamicSharedMemorySize, SM_RESB);
    cudaFuncSetAttribute(attn_kernel, cudaFuncAttributeMaxDynamicSharedMemorySize, ATT_LSMEM);
    cudaFuncSetAttribute(GK_GLU, cudaFuncAttributeMaxDynamicSharedMemorySize, SM_GLU);
    cudaFuncSetAttribute(rec_kernel, cudaFuncAttributeMaxDynamicSharedMemorySize, rc::SMEM);
    cudaFuncAttributes fa;
    cudaFuncGetAttributes(&fa, mod_kernel); cudaFuncGetAttributes(&fa, ln_kernel); cudaFuncGetAttributes(&fa, attn_kernel);
    cudaFuncGetAttributes(&fa, rec_kernel); cudaFuncGetAttributes(&fa, GK_QKV);
    cudaFuncGetAttributes(&fa, GK_RES); cudaFuncGetAttributes(&fa, GK_GLU);
    int lo = 0, hi = 0;
    cudaDeviceGetStreamPriorityRange(&lo, &hi);
    cudaStreamCreateWithPriority(&s_rec, cudaStreamNonBlocking, hi);
    cudaStreamCreateWithPriority(&s_att, cudaStreamNonBlocking, lo);
    cudaEventCreateWithFlags(&s_evFork2, cudaEventDisableTiming);
    cudaEventCreateWithFlags(&s_evJoin2, cudaEventDisableTiming);
    cudaEventCreateWithFlags(&s_evJoin3, cudaEventDisableTiming);
    cudaFuncGetAttributes(&fa, GK_RES64);
    cudaFuncGetAttributes(&fa, gate_kernel);
    cudaFuncSetAttribute(gate_kernel, cudaFuncAttributePreferredSharedMemoryCarveout, 100);
    cudaFuncSetAttribute(GK_QKV, cudaFuncAttributePreferredSharedMemoryCarveout, 100);
    cudaFuncSetAttribute(GK_RES, cudaFuncAttributePreferredSharedMemoryCarveout, 100);
    cudaFuncSetAttribute(GK_RES64, cudaFuncAttributePreferredSharedMemoryCarveout, 100);
    cudaFuncSetAttribute(GK_GLU, cudaFuncAttributePreferredSharedMemoryCarveout, 100);
    cudaFuncSetAttribute(attn_kernel, cudaFuncAttributePreferredSharedMemoryCarveout, 100);
    cudaFuncSetAttribute(ln_kernel, cudaFuncAttributePreferredSharedMemoryCarveout, 100);
    cudaFuncSetAttribute(mod_kernel, cudaFuncAttributePreferredSharedMemoryCarveout, 100);
    cudaEventCreateWithFlags(&s_evFork, cudaEventDisableTiming);
    cudaEventCreateWithFlags(&s_evJoin, cudaEventDisableTiming);
    init = true;
  }
  CUtensorMap mA_h = make_map(p_h, DM, S_TOK, 64, 128);
  CUtensorMap mB_q = make_map(Wq, HD, DM, 64, 64), mB_k = make_map(Wk, HD, DM, 64, 64), mB_v = make_map(Wv, HD, DM, 64, 64);
  CUtensorMap mA_o = make_map(p_o, HD, S_TOK, 64, 128), mB_o = make_map(Wo, DM, HD, 64, 64);
  CUtensorMap mA_o64 = make_map(p_o, HD, S_TOK, 64, 64);
  CUtensorMap mA_h2 = make_map(p_h2, DM, S_TOK, 64, 128);
  CUtensorMap mB_g = make_map(w_gate, FF, DM, 64, 64), mB_u = make_map(w_up, FF, DM, 64, 64);
  CUtensorMap mA_act = make_map(p_act, FF, S_TOK, 64, 128), mB_d = make_map(w_down, DM, FF, 64, 64);

  cudaStream_t st = cudaStreamPerThread;
  mod_kernel<<<120, 256, 0, st>>>(cvec, w_mod);
  cudaEventRecord(s_evFork, st);
  cudaStreamWaitEvent(s_rec, s_evFork, 0);
  rec_kernel<<<rc::NCTA, 384, rc::SMEM, s_rec>>>(Wq, Wk, Wv, Wo, mem0);
  cudaEventRecord(s_evJoin, s_rec);
  ln_kernel<<<S_TOK / 8, 256, 0, st>>>(x, (bf16*)p_h, 0, DM, rc::NCTA, 0);
  cudaEventRecord(s_evFork2, st);
  cudaStreamWaitEvent(s_att, s_evFork2, 0);
  gate_kernel<<<1, 1, 0, s_att>>>(SHADOW_CTAS);
  attn_kernel<<<NH * NSEG / 2, 128, ATT_LSMEM, s_att>>>();
  cudaEventRecord(s_evJoin2, s_att);
  {
    GemmP p{16, 48, 10, 0, nullptr, nullptr, 0, 2, 1, 16, 0};
    GK_QKV<<<SHADOW_CTAS, 288, SM_QKV, st>>>(mA_h, mB_q, mB_k, mB_v, p);
  }
  cudaStreamWaitEvent(st, s_evJoin, 0);
  cudaStreamWaitEvent(st, s_evJoin2, 0);

  {
    GemmP p{16, 5, 64, 0, x, (bf16*)p_x1, 2 * DM, 0, 0, 0, 0};
    GK_RESB<<<80, 288, SM_RESB, st>>>(mA_o, mB_o, mB_o, mB_o, p);
  }
  ln_kernel<<<S_TOK / 8, 256, 0, st>>>((const bf16*)p_x1, (bf16*)p_h2, 3 * DM, 4 * DM, 0, 1);
  {
    GemmP p{16, 27, 10, 0, nullptr, nullptr, 0, 0, 0, 0, 0};
    GK_GLU<<<264, 288, SM_GLU, st>>>(mA_h2, mB_g, mB_u, mB_u, p);
  }
  {
    GemmP p{16, 5, 27, 0, (const bf16*)p_x1, out, 5 * DM, 0, 0, 0, 0};
    GK_RESB<<<80, 288, SM_RESB, st>>>(mA_act, mB_d, mB_d, mB_d, p);
  }
}
```

```cpp
#include <cuda_runtime.h>
#include <cuda_bf16.h>
#include <cuda.h>
#include <stdint.h>

typedef __nv_bfloat16 bf16;

constexpr int S_TOK = 2048, DM = 640, NH = 32, DH = 128, NMEM = 8, SEG = 32, NSEG = 64, FF = 1728;
constexpr int HD = NH * DH;

__device__ float g_mod[6 * DM];
__device__ __align__(1024) bf16 g_h[S_TOK * DM];
__device__ __align__(1024) bf16 g_q[NH * S_TOK * DH];
__device__ __align__(1024) bf16 g_k[NH * S_TOK * DH];
__device__ __align__(1024) bf16 g_v[NH * S_TOK * DH];
__device__ __align__(1024) bf16 g_km[NSEG * NH * NMEM * DH];
__device__ __align__(1024) bf16 g_vm[NSEG * NH * NMEM * DH];
__device__ __align__(1024) bf16 g_o[S_TOK * HD];
__device__ __align__(1024) bf16 g_x1[S_TOK * DM];
__device__ __align__(1024) float g_wpart[3 * S_TOK * DM];
__device__ __align__(1024) bf16 g_h2[S_TOK * DM];
__device__ __align__(1024) bf16 g_act[S_TOK * FF];
__device__ __align__(1024) float g_part[2 * 40 * 8 * 32 * 16];
__device__ __align__(1024) uint32_t g_memb[4 * 2560];
__device__ int g_err;
__device__ unsigned g_kvflag[16 * 96];
__device__ unsigned g_resident;
__device__ unsigned g_ready;
__device__ unsigned g_resident2;
__device__ unsigned g_oflag[16];
__device__ unsigned g_mflag[NSEG * NH];

#define TL_START(id)
#define TL_END(id)
__device__ __forceinline__ uint32_t smem_u32(const void* p) { return (uint32_t)__cvta_generic_to_shared(p); }
__device__ __forceinline__ uint32_t pack2(float lo, float hi) {
  uint32_t r; asm("cvt.rn.bf16x2.f32 %0, %1, %2;" : "=r"(r) : "f"(hi), "f"(lo)); return r;
}
__device__ __forceinline__ float bfr(float x) { return __uint_as_float(pack2(0.f, x) & 0xffff0000u); }
__device__ __forceinline__ float lo2f(uint32_t v) { return __uint_as_float(v << 16); }
__device__ __forceinline__ float hi2f(uint32_t v) { return __uint_as_float(v & 0xffff0000u); }

__device__ __forceinline__ void mbar_init(uint32_t bar, uint32_t cnt) {
  asm volatile("mbarrier.init.shared::cta.b64 [%0], %1;" ::"r"(bar), "r"(cnt) : "memory");
}
__device__ __forceinline__ void mbar_expect_tx(uint32_t bar, uint32_t bytes) {
  asm volatile("mbarrier.arrive.expect_tx.shared::cta.b64 _, [%0], %1;" ::"r"(bar), "r"(bytes) : "memory");
}
__device__ __forceinline__ void mbar_arrive(uint32_t bar) {
  asm volatile("mbarrier.arrive.shared::cta.b64 _, [%0];" ::"r"(bar) : "memory");
}
__device__ __forceinline__ bool mbar_try(uint32_t bar, uint32_t parity) {
  uint32_t ok;
  asm volatile("{\n.reg .pred p;\nmbarrier.try_wait.parity.shared::cta.b64 p, [%1], %2;\nselp.u32 %0,1,0,p;\n}"
               : "=r"(ok) : "r"(bar), "r"(parity) : "memory");
  return ok != 0;
}
__device__ __forceinline__ void mbar_wait(uint32_t bar, uint32_t parity) {
  int guard = 0;
  while (!mbar_try(bar, parity)) { if (++guard > (1 << 24)) { g_err = 1; __trap(); } }
}
__device__ __forceinline__ void mbar_wait_cluster(uint32_t bar, uint32_t parity) {
  int guard = 0; uint32_t ok;
  do {
    asm volatile("{\n.reg .pred p;\nmbarrier.try_wait.parity.acquire.cluster.shared::cta.b64 p, [%1], %2;\nselp.u32 %0,1,0,p;\n}"
                 : "=r"(ok) : "r"(bar), "r"(parity) : "memory");
    if (++guard > (1 << 24)) { g_err = 2; __trap(); }
  } while (!ok);
}
__device__ __forceinline__ void tma_load_2d(uint32_t dst, const CUtensorMap* map, int x, int y, uint32_t bar) {
  asm volatile("cp.async.bulk.tensor.2d.shared::cluster.global.mbarrier::complete_tx::bytes [%0], [%1, {%3, %4}], [%2];"
               ::"r"(dst), "l"((uint64_t)map), "r"(bar), "r"(x), "r"(y) : "memory");
}
__device__ __forceinline__ void tma_load_2d_mc(uint32_t dst, const CUtensorMap* map, int x, int y, uint32_t bar, uint16_t mask) {
  asm volatile("cp.async.bulk.tensor.2d.shared::cluster.global.mbarrier::complete_tx::bytes.multicast::cluster [%0], [%1, {%3, %4}], [%2], %5;"
               ::"r"(dst), "l"((uint64_t)map), "r"(bar), "r"(x), "r"(y), "h"(mask) : "memory");
}
__device__ __forceinline__ void mbar_arrive_cluster(uint32_t bar_cluster_addr) {
  asm volatile("mbarrier.arrive.shared::cluster.b64 _, [%0];" ::"r"(bar_cluster_addr) : "memory");
}
__device__ __forceinline__ void bulk_g2s(uint32_t dst, const void* src, uint32_t bytes, uint32_t bar) {
  asm volatile("cp.async.bulk.shared::cluster.global.mbarrier::complete_tx::bytes [%0], [%1], %2, [%3];"
               ::"r"(dst), "l"((uint64_t)src), "r"(bytes), "r"(bar) : "memory");
}
__device__ __forceinline__ void bulk_s2g(void* dst, uint32_t src, uint32_t bytes) {
  asm volatile("cp.async.bulk.global.shared::cta.bulk_group [%0], [%1], %2;" ::"l"((uint64_t)dst), "r"(src), "r"(bytes) : "memory");
}
__device__ __forceinline__ void bulk_commit() { asm volatile("cp.async.bulk.commit_group;" ::: "memory"); }
__device__ __forceinline__ void bulk_wait_read0() { asm volatile("cp.async.bulk.wait_group.read 0;" ::: "memory"); }
__device__ __forceinline__ void bulk_wait0() { asm volatile("cp.async.bulk.wait_group 0;" ::: "memory"); }
__device__ __forceinline__ void fence_async_smem() { asm volatile("fence.proxy.async.shared::cta;" ::: "memory"); }
__device__ __forceinline__ void wg_fence() { asm volatile("wgmma.fence.sync.aligned;" ::: "memory"); }
__device__ __forceinline__ void wg_commit() { asm volatile("wgmma.commit_group.sync.aligned;" ::: "memory"); }
template <int N> __device__ __forceinline__ void wg_wait() { asm volatile("wgmma.wait_group.sync.aligned %0;" ::"n"(N) : "memory"); }
__device__ __forceinline__ void bar_sync(int id, int n) { asm volatile("bar.sync %0, %1;" ::"r"(id), "r"(n) : "memory"); }

__device__ __forceinline__ void mma16816(float* c, uint32_t a0, uint32_t a1, uint32_t a2, uint32_t a3, uint32_t b0, uint32_t b1) {
  asm volatile("mma.sync.aligned.m16n8k16.row.col.f32.bf16.bf16.f32 {%0,%1,%2,%3},{%4,%5,%6,%7},{%8,%9},{%0,%1,%2,%3};"
               : "+f"(c[0]), "+f"(c[1]), "+f"(c[2]), "+f"(c[3]) : "r"(a0), "r"(a1), "r"(a2), "r"(a3), "r"(b0), "r"(b1));
}
__device__ __forceinline__ void ldsm4(uint32_t* r, uint32_t addr) {
  asm volatile("ldmatrix.sync.aligned.m8n8.x4.shared.b16 {%0,%1,%2,%3}, [%4];"
               : "=r"(r[0]), "=r"(r[1]), "=r"(r[2]), "=r"(r[3]) : "r"(addr) : "memory");
}
__device__ __forceinline__ void ldsm4t(uint32_t* r, uint32_t addr) {
  asm volatile("ldmatrix.sync.aligned.m8n8.x4.trans.shared.b16 {%0,%1,%2,%3}, [%4];"
               : "=r"(r[0]), "=r"(r[1]), "=r"(r[2]), "=r"(r[3]) : "r"(addr) : "memory");
}
__device__ __forceinline__ void ldsm2(uint32_t* r, uint32_t addr) {
  asm volatile("ldmatrix.sync.aligned.m8n8.x2.shared.b16 {%0,%1}, [%2];" : "=r"(r[0]), "=r"(r[1]) : "r"(addr) : "memory");
}
__device__ __forceinline__ void ldsm2t(uint32_t* r, uint32_t addr) {
  asm volatile("ldmatrix.sync.aligned.m8n8.x2.trans.shared.b16 {%0,%1}, [%2];" : "=r"(r[0]), "=r"(r[1]) : "r"(addr) : "memory");
}
__device__ __forceinline__ void stsm4(uint32_t addr, uint32_t r0, uint32_t r1, uint32_t r2, uint32_t r3) {
  asm volatile("stmatrix.sync.aligned.m8n8.x4.shared.b16 [%0], {%1,%2,%3,%4};" ::"r"(addr), "r"(r0), "r"(r1), "r"(r2), "r"(r3) : "memory");
}
__device__ __forceinline__ uint32_t movtrans(uint32_t a) {
  uint32_t d; asm volatile("movmatrix.sync.aligned.m8n8.trans.b16 %0, %1;" : "=r"(d) : "r"(a)); return d;
}
__device__ __forceinline__ uint4 lds128(uint32_t a) {
  uint4 v; asm volatile("ld.shared.v4.u32 {%0,%1,%2,%3}, [%4];" : "=r"(v.x), "=r"(v.y), "=r"(v.z), "=r"(v.w) : "r"(a) : "memory"); return v;
}
__device__ __forceinline__ float4 lds128f(uint32_t a) {
  float4 v; asm volatile("ld.shared.v4.f32 {%0,%1,%2,%3}, [%4];" : "=f"(v.x), "=f"(v.y), "=f"(v.z), "=f"(v.w) : "r"(a) : "memory"); return v;
}
__device__ __forceinline__ uint2 lds64(uint32_t a) {
  uint2 v; asm volatile("ld.shared.v2.u32 {%0,%1}, [%2];" : "=r"(v.x), "=r"(v.y) : "r"(a) : "memory"); return v;
}
__device__ __forceinline__ void sts128(uint32_t a, uint32_t x, uint32_t y, uint32_t z, uint32_t w) {
  asm volatile("st.shared.v4.u32 [%0], {%1,%2,%3,%4};" ::"r"(a), "r"(x), "r"(y), "r"(z), "r"(w) : "memory");
}
__device__ __forceinline__ void sts128f(uint32_t a, const float* c) {
  asm volatile("st.shared.v4.f32 [%0], {%1,%2,%3,%4};" ::"r"(a), "f"(c[0]), "f"(c[1]), "f"(c[2]), "f"(c[3]) : "memory");
}
__device__ __forceinline__ void sts64(uint32_t a, uint32_t x, uint32_t y) {
  asm volatile("st.shared.v2.u32 [%0], {%1,%2};" ::"r"(a), "r"(x), "r"(y) : "memory");
}
__device__ __forceinline__ uint4 ldg_relaxed128(const void* p) {
  uint4 v; asm volatile("ld.relaxed.gpu.global.v4.u32 {%0,%1,%2,%3}, [%4];" : "=r"(v.x), "=r"(v.y), "=r"(v.z), "=r"(v.w) : "l"(p) : "memory"); return v;
}
__device__ __forceinline__ void stg_relaxed128(void* p, uint32_t x, uint32_t y, uint32_t z, uint32_t w) {
  asm volatile("st.relaxed.gpu.global.v4.u32 [%0], {%1,%2,%3,%4};" ::"l"(p), "r"(x), "r"(y), "r"(z), "r"(w) : "memory");
}
__device__ __forceinline__ void stg_relaxed32(void* p, uint32_t x) {
  asm volatile("st.relaxed.gpu.global.u32 [%0], %1;" ::"l"(p), "r"(x) : "memory");
}
__device__ __forceinline__ uint32_t ld_acquire32(const void* p) {
  uint32_t v; asm volatile("ld.acquire.gpu.global.u32 %0, [%1];" : "=r"(v) : "l"(p) : "memory"); return v;
}
__device__ __forceinline__ void red_release_add(void* p, uint32_t v) {
  asm volatile("red.release.gpu.global.add.u32 [%0], %1;" ::"l"(p), "r"(v) : "memory");
}
__device__ __forceinline__ void fence_async_all() { asm volatile("fence.proxy.async;" ::: "memory"); }
__device__ __forceinline__ uint32_t mapa(uint32_t a, uint32_t rank) {
  uint32_t r; asm volatile("mapa.shared::cluster.u32 %0, %1, %2;" : "=r"(r) : "r"(a), "r"(rank)); return r;
}
__device__ __forceinline__ void st_async128(uint32_t a, uint32_t x, uint32_t y, uint32_t z, uint32_t w, uint32_t bar) {
  asm volatile("st.async.weak.shared::cluster.mbarrier::complete_tx::bytes.v4.u32 [%0], {%1,%2,%3,%4}, [%5];"
               ::"r"(a), "r"(x), "r"(y), "r"(z), "r"(w), "r"(bar) : "memory");
}
__device__ __forceinline__ void st_async64(uint32_t a, uint32_t x, uint32_t y, uint32_t bar) {
  asm volatile("st.async.weak.shared::cluster.mbarrier::complete_tx::bytes.v2.u32 [%0], {%1,%2}, [%3];"
               ::"r"(a), "r"(x), "r"(y), "r"(bar) : "memory");
}
__device__ __forceinline__ void cp_async16(uint32_t dst, const void* src) {
  asm volatile("cp.async.cg.shared.global [%0], [%1], 16;" ::"r"(dst), "l"(src) : "memory");
}
__device__ __forceinline__ void cp_async_wait_all() { asm volatile("cp.async.wait_all;" ::: "memory"); }

__device__ __forceinline__ void wgmma_n128(float* d, uint64_t da, uint64_t db, int scale_d) {
  asm volatile("{\n.reg .pred p;\nsetp.ne.b32 p, %66, 0;\n"
    "wgmma.mma_async.sync.aligned.m64n128k16.f32.bf16.bf16 {%0,%1,%2,%3,%4,%5,%6,%7,%8,%9,%10,%11,%12,%13,%14,%15,%16,%17,%18,%19,%20,%21,%22,%23,%24,%25,%26,%27,%28,%29,%30,%31,%32,%33,%34,%35,%36,%37,%38,%39,%40,%41,%42,%43,%44,%45,%46,%47,%48,%49,%50,%51,%52,%53,%54,%55,%56,%57,%58,%59,%60,%61,%62,%63}, %64, %65, p, 1, 1, 0, 1;\n}\n"
    : "+f"(d[0]),"+f"(d[1]),"+f"(d[2]),"+f"(d[3]),"+f"(d[4]),"+f"(d[5]),"+f"(d[6]),"+f"(d[7]),"+f"(d[8]),"+f"(d[9]),"+f"(d[10]),"+f"(d[11]),"+f"(d[12]),"+f"(d[13]),"+f"(d[14]),"+f"(d[15]),"+f"(d[16]),"+f"(d[17]),"+f"(d[18]),"+f"(d[19]),"+f"(d[20]),"+f"(d[21]),"+f"(d[22]),"+f"(d[23]),"+f"(d[24]),"+f"(d[25]),"+f"(d[26]),"+f"(d[27]),"+f"(d[28]),"+f"(d[29]),"+f"(d[30]),"+f"(d[31]),"+f"(d[32]),"+f"(d[33]),"+f"(d[34]),"+f"(d[35]),"+f"(d[36]),"+f"(d[37]),"+f"(d[38]),"+f"(d[39]),"+f"(d[40]),"+f"(d[41]),"+f"(d[42]),"+f"(d[43]),"+f"(d[44]),"+f"(d[45]),"+f"(d[46]),"+f"(d[47]),"+f"(d[48]),"+f"(d[49]),"+f"(d[50]),"+f"(d[51]),"+f"(d[52]),"+f"(d[53]),"+f"(d[54]),"+f"(d[55]),"+f"(d[56]),"+f"(d[57]),"+f"(d[58]),"+f"(d[59]),"+f"(d[60]),"+f"(d[61]),"+f"(d[62]),"+f"(d[63])
    : "l"(da), "l"(db), "r"(scale_d));
}

__device__ __forceinline__ void wgmma_n256(float* d, uint64_t da, uint64_t db, int scale_d) {
  asm volatile("{\n.reg .pred p;\nsetp.ne.b32 p, %130, 0;\n"
    "wgmma.mma_async.sync.aligned.m64n256k16.f32.bf16.bf16 {%0,%1,%2,%3,%4,%5,%6,%7,%8,%9,%10,%11,%12,%13,%14,%15,%16,%17,%18,%19,%20,%21,%22,%23,%24,%25,%26,%27,%28,%29,%30,%31,%32,%33,%34,%35,%36,%37,%38,%39,%40,%41,%42,%43,%44,%45,%46,%47,%48,%49,%50,%51,%52,%53,%54,%55,%56,%57,%58,%59,%60,%61,%62,%63,%64,%65,%66,%67,%68,%69,%70,%71,%72,%73,%74,%75,%76,%77,%78,%79,%80,%81,%82,%83,%84,%85,%86,%87,%88,%89,%90,%91,%92,%93,%94,%95,%96,%97,%98,%99,%100,%101,%102,%103,%104,%105,%106,%107,%108,%109,%110,%111,%112,%113,%114,%115,%116,%117,%118,%119,%120,%121,%122,%123,%124,%125,%126,%127}, %128, %129, p, 1, 1, 0, 1;\n}\n"
    : "+f"(d[0]),"+f"(d[1]),"+f"(d[2]),"+f"(d[3]),"+f"(d[4]),"+f"(d[5]),"+f"(d[6]),"+f"(d[7]),"+f"(d[8]),"+f"(d[9]),"+f"(d[10]),"+f"(d[11]),"+f"(d[12]),"+f"(d[13]),"+f"(d[14]),"+f"(d[15]),"+f"(d[16]),"+f"(d[17]),"+f"(d[18]),"+f"(d[19]),"+f"(d[20]),"+f"(d[21]),"+f"(d[22]),"+f"(d[23]),"+f"(d[24]),"+f"(d[25]),"+f"(d[26]),"+f"(d[27]),"+f"(d[28]),"+f"(d[29]),"+f"(d[30]),"+f"(d[31]),"+f"(d[32]),"+f"(d[33]),"+f"(d[34]),"+f"(d[35]),"+f"(d[36]),"+f"(d[37]),"+f"(d[38]),"+f"(d[39]),"+f"(d[40]),"+f"(d[41]),"+f"(d[42]),"+f"(d[43]),"+f"(d[44]),"+f"(d[45]),"+f"(d[46]),"+f"(d[47]),"+f"(d[48]),"+f"(d[49]),"+f"(d[50]),"+f"(d[51]),"+f"(d[52]),"+f"(d[53]),"+f"(d[54]),"+f"(d[55]),"+f"(d[56]),"+f"(d[57]),"+f"(d[58]),"+f"(d[59]),"+f"(d[60]),"+f"(d[61]),"+f"(d[62]),"+f"(d[63]),"+f"(d[64]),"+f"(d[65]),"+f"(d[66]),"+f"(d[67]),"+f"(d[68]),"+f"(d[69]),"+f"(d[70]),"+f"(d[71]),"+f"(d[72]),"+f"(d[73]),"+f"(d[74]),"+f"(d[75]),"+f"(d[76]),"+f"(d[77]),"+f"(d[78]),"+f"(d[79]),"+f"(d[80]),"+f"(d[81]),"+f"(d[82]),"+f"(d[83]),"+f"(d[84]),"+f"(d[85]),"+f"(d[86]),"+f"(d[87]),"+f"(d[88]),"+f"(d[89]),"+f"(d[90]),"+f"(d[91]),"+f"(d[92]),"+f"(d[93]),"+f"(d[94]),"+f"(d[95]),"+f"(d[96]),"+f"(d[97]),"+f"(d[98]),"+f"(d[99]),"+f"(d[100]),"+f"(d[101]),"+f"(d[102]),"+f"(d[103]),"+f"(d[104]),"+f"(d[105]),"+f"(d[106]),"+f"(d[107]),"+f"(d[108]),"+f"(d[109]),"+f"(d[110]),"+f"(d[111]),"+f"(d[112]),"+f"(d[113]),"+f"(d[114]),"+f"(d[115]),"+f"(d[116]),"+f"(d[117]),"+f"(d[118]),"+f"(d[119]),"+f"(d[120]),"+f"(d[121]),"+f"(d[122]),"+f"(d[123]),"+f"(d[124]),"+f"(d[125]),"+f"(d[126]),"+f"(d[127])
    : "l"(da), "l"(db), "r"(scale_d));
}

__global__ void __launch_bounds__(256) mod_kernel(const bf16* __restrict__ c, const bf16* __restrict__ w_mod) {
  __shared__ float s_c[DM];
  __shared__ float s_red[64][33];
  const int tid = threadIdx.x;
  TL_START(0);
  for (int i = tid; i < DM; i += 256) {
    float v = __bfloat162float(c[i]);
    s_c[i] = bfr(v / (1.f + __expf(-v)));
  }
  __syncthreads();
  {
    const int cg = tid & 3, kg = tid >> 2;
    const int col0 = blockIdx.x * 32 + cg * 8;
    float acc[8];
#pragma unroll
    for (int j = 0; j < 8; j++) acc[j] = 0.f;
    uint4 w[10];
#pragma unroll
    for (int i = 0; i < 10; i++) w[i] = *reinterpret_cast<const uint4*>(w_mod + (size_t)(kg * 10 + i) * (6 * DM) + col0);
#pragma unroll
    for (int i = 0; i < 10; i++) {
      float cv = s_c[kg * 10 + i];
      acc[0] += cv * lo2f(w[i].x); acc[1] += cv * hi2f(w[i].x);
      acc[2] += cv * lo2f(w[i].y); acc[3] += cv * hi2f(w[i].y);
      acc[4] += cv * lo2f(w[i].z); acc[5] += cv * hi2f(w[i].z);
      acc[6] += cv * lo2f(w[i].w); acc[7] += cv * hi2f(w[i].w);
    }
#pragma unroll
    for (int j = 0; j < 8; j++) s_red[kg][cg * 8 + j] = acc[j];
  }
  __syncthreads();
  if (tid < 32) {
    float s = 0.f;
    for (int i = 0; i < 64; i++) s += s_red[i][tid];
    g_mod[blockIdx.x * 32 + tid] = bfr(s);
  }
  TL_END(0);
}

__global__ void __launch_bounds__(256) ln_kernel(const bf16* __restrict__ x, bf16* __restrict__ out, int shift_off, int scale_off, unsigned gate, int reset,
                                                 bf16* __restrict__ x1out) {
  const int warp = threadIdx.x >> 5, lane = threadIdx.x & 31;
  const int row = blockIdx.x * 8 + warp;
  asm volatile("griddepcontrol.launch_dependents;");
  asm volatile("griddepcontrol.wait;" ::: "memory");
  TL_START(reset ? 6 : 1);
  const uint2* xr = reinterpret_cast<const uint2*>(x + (size_t)row * DM);
  float v[20];
#pragma unroll
  for (int i = 0; i < 5; i++) {
    uint2 u = xr[i * 32 + lane];
    v[i * 4 + 0] = lo2f(u.x); v[i * 4 + 1] = hi2f(u.x); v[i * 4 + 2] = lo2f(u.y); v[i * 4 + 3] = hi2f(u.y);
  }
  if (x1out) {
#pragma unroll
    for (int i = 0; i < 5; i++) {
      const int col = (i * 32 + lane) * 4;
      const float* pp = g_wpart + (size_t)row * DM + col;
      const float4 a = *reinterpret_cast<const float4*>(pp), b = *reinterpret_cast<const float4*>(pp + (size_t)S_TOK * DM);
      const float4 c = *reinterpret_cast<const float4*>(pp + (size_t)2 * S_TOK * DM);
      const float4 g = *reinterpret_cast<const float4*>(g_mod + 2 * DM + col);
      v[i * 4 + 0] = bfr(v[i * 4 + 0] + bfr(g.x * bfr(a.x + b.x + c.x)));
      v[i * 4 + 1] = bfr(v[i * 4 + 1] + bfr(g.y * bfr(a.y + b.y + c.y)));
      v[i * 4 + 2] = bfr(v[i * 4 + 2] + bfr(g.z * bfr(a.z + b.z + c.z)));
      v[i * 4 + 3] = bfr(v[i * 4 + 3] + bfr(g.w * bfr(a.w + b.w + c.w)));
      reinterpret_cast<uint2*>(x1out + (size_t)row * DM)[i * 32 + lane] = make_uint2(pack2(v[i * 4], v[i * 4 + 1]), pack2(v[i * 4 + 2], v[i * 4 + 3]));
    }
  }
  float s = 0.f;
#pragma unroll
  for (int i = 0; i < 20; i++) s += v[i];
#pragma unroll
  for (int o = 16; o; o >>= 1) s += __shfl_xor_sync(~0u, s, o);
  const float mean = s * (1.f / DM);
  float q = 0.f;
#pragma unroll
  for (int i = 0; i < 20; i++) { float d = v[i] - mean; q += d * d; }
#pragma unroll
  for (int o = 16; o; o >>= 1) q += __shfl_xor_sync(~0u, q, o);
  const float mb = bfr(mean);
  const float den = bfr(sqrtf(bfr(bfr(q * (1.f / DM)) + 1e-5f)));
  uint2* orow = reinterpret_cast<uint2*>(out + (size_t)row * DM);
#pragma unroll
  for (int i = 0; i < 5; i++) {
    const int col = (i * 32 + lane) * 4;
    float4 sh = *reinterpret_cast<const float4*>(g_mod + shift_off + col);
    float4 sc = *reinterpret_cast<const float4*>(g_mod + scale_off + col);
    float r0 = bfr(bfr(bfr(v[i * 4 + 0] - mb) / den) * bfr(1.f + sc.x)) + sh.x;
    float r1 = bfr(bfr(bfr(v[i * 4 + 1] - mb) / den) * bfr(1.f + sc.y)) + sh.y;
    float r2 = bfr(bfr(bfr(v[i * 4 + 2] - mb) / den) * bfr(1.f + sc.z)) + sh.z;
    float r3 = bfr(bfr(bfr(v[i * 4 + 3] - mb) / den) * bfr(1.f + sc.w)) + sh.w;
    orow[i * 32 + lane] = make_uint2(pack2(r0, r1), pack2(r2, r3));
  }
  if (reset) {
    const int gt = blockIdx.x * 256 + threadIdx.x;
    if (gt < 16 * 96) g_kvflag[gt] = 0;
    if (gt < NSEG * NH) g_mflag[gt] = 0;
    if (gt < 16) g_oflag[gt] = 0;
    if (gt == 0) { g_resident = 0; g_resident2 = 0; g_ready = 0; }
  }
  if (gate && blockIdx.x == 0 && threadIdx.x == 0) {
    for (int i = 0; i < 20000 && ld_acquire32(&g_resident) < gate; i++) __nanosleep(50);
  }
  TL_END(reset ? 6 : 1);
}

enum { EPI_QKV = 0, EPI_RES = 1, EPI_GEGLU = 2, EPI_PART = 3 };
struct GemmP {
  int m_tiles, n_tiles, kblocks;
  int n_off;
  const bf16* res;
  bf16* out;
  int gate_off;
  int m_major;
  int use_flags;
  int n_rot;
  int m_off;
  int signal;
};
__device__ __forceinline__ void tile_coords(const GemmP& p, int t, int& mt, int& nt) {
  if (p.m_major == 2) {
    if (t < 32) { mt = 0; nt = 16 + t; return; }
    const int u = t - 32, b = u / 48, r = u % 48;
    const int lastb = p.m_tiles - 1;
    if (b < lastb && r < 32) { mt = b + 1; nt = 16 + r; }
    else { mt = b; nt = b < lastb ? r - 32 : r; }
    return;
  }
  mt = p.m_off + (p.m_major ? t / p.n_tiles : t % p.m_tiles);
  nt = p.m_major ? (t % p.n_tiles + p.n_rot) % p.n_tiles : t / p.m_tiles;
}
template <int BN, int NST, int STGW = 4096, int BM = 128> struct GemmCfg {
  static constexpr int STAGES = NST;
  static constexpr int A_BYTES = BM * 64 * 2, B_BYTES = BN * 64 * 2, STAGE = A_BYTES + B_BYTES;
  static constexpr int STG_OFF = STAGES * STAGE;
  static constexpr int BAR_OFF = STG_OFF + (BM / 16) * STGW;
  static constexpr int SMEM = BAR_OFF + 128;
};
__device__ __forceinline__ float gelu_tanh(float x) {
  const float u = x * fmaf(x * x, 0.7978845608028654f * 0.044715f, 0.7978845608028654f);
  float e; asm("ex2.approx.ftz.f32 %0, %1;" : "=f"(e) : "f"(u * (-2.f * 1.4426950408889634f)));
  return __fdividef(x, 1.f + e);
}

template <int BN, int EPI, int NST, int LBT, int LBB, int RC, int BM = 128, int MC = 0>
__global__ void __launch_bounds__(LBT, LBB)
gemm_kernel(const __grid_constant__ CUtensorMap tmA, const __grid_constant__ CUtensorMap tmB0,
            const __grid_constant__ CUtensorMap tmB1, const __grid_constant__ CUtensorMap tmB2, GemmP p) {
  constexpr int STGW = EPI == EPI_QKV ? 8192 : (EPI == EPI_RES ? 4096 : 2048);
  using C = GemmCfg<BN, NST, STGW, BM>;
  constexpr int NCW = BM / 16;
  extern __shared__ __align__(1024) uint8_t smem_raw[];
  const uint32_t sb = smem_u32(smem_raw);
  if (sb & 1023u) __trap();
  const uint32_t full0 = sb + C::BAR_OFF, empty0 = full0 + 8 * C::STAGES;
  const int warp = threadIdx.x >> 5, lane = threadIdx.x & 31;
  const int tlid = EPI == EPI_QKV ? 2 : (EPI == EPI_GEGLU ? 7 : (p.kblocks == 64 ? 5 : 8));
  (void)tlid;
  TL_START(tlid);
  if (threadIdx.x == 0) {
    for (int i = 0; i < C::STAGES; i++) { mbar_init(full0 + 8 * i, 1); mbar_init(empty0 + 8 * i, NCW * (MC + 1)); }
    asm volatile("fence.mbarrier_init.release.cluster;" ::: "memory");
    if (p.use_flags || p.signal) atomicAdd(&g_resident2, 1u);
  }
  __syncthreads();
  if (EPI != EPI_QKV) {
    asm volatile("griddepcontrol.launch_dependents;");
    asm volatile("griddepcontrol.wait;" ::: "memory");
  }
  if (MC) asm volatile("barrier.cluster.arrive.aligned;\nbarrier.cluster.wait.aligned;" ::: "memory");
  const int crank = MC ? (blockIdx.x & 1) : 0;
  const int t0 = MC ? blockIdx.x >> 1 : blockIdx.x, tstep = MC ? gridDim.x >> 1 : gridDim.x;
  const int ntiles = p.m_tiles * p.n_tiles;
  if (warp >= NCW) {
    if (RC > 1) asm volatile("setmaxnreg.dec.sync.aligned.u32 24;");
    if (warp == NCW && lane == 0) {
      int st = 0; uint32_t ph = 1;
      for (int t = t0; t < ntiles; t += tstep) {
        int mt, nt; tile_coords(p, t, mt, nt);
        if (MC) mt = 2 * mt + crank;
        const int gn = (nt + p.n_off) * BN, mat = gn / HD;
        const CUtensorMap* mp = (EPI != EPI_QKV || mat == 0) ? &tmB0 : (mat == 1 ? &tmB1 : &tmB2);
        const int col = EPI == EPI_QKV ? gn % HD : (EPI == EPI_GEGLU ? nt * (BN / 2) : (EPI == EPI_PART ? (nt % 5) * BN : nt * BN));
        const int kb0 = EPI == EPI_PART ? (nt / 5) * 21 + (nt >= 5) : 0, kb1 = EPI == EPI_PART ? (nt / 5) * 21 + 22 : p.kblocks;
        for (int kb = kb0; kb < kb1; kb++) {
          mbar_wait(empty0 + 8 * st, ph);
          const uint32_t fb = full0 + 8 * st, sa = sb + st * C::STAGE, sbb = sa + C::A_BYTES;
          mbar_expect_tx(fb, C::STAGE);
          tma_load_2d(sa, &tmA, kb * 64, mt * BM, fb);
          if (MC) {
#pragma unroll
            for (int i = 0; i < BN / 128; i++) {
              if (EPI == EPI_GEGLU) tma_load_2d_mc(sbb + (2 * i + crank) * 8192, crank ? &tmB1 : &tmB0, col + i * 64, kb * 64, fb, 3);
              else { const int b = crank * (BN / 128) + i; tma_load_2d_mc(sbb + b * 8192, mp, col + b * 64, kb * 64, fb, 3); }
            }
          } else if (EPI == EPI_GEGLU) {
#pragma unroll
            for (int b = 0; b < BN / 128; b++) {
              tma_load_2d(sbb + (2 * b) * 8192, &tmB0, col + b * 64, kb * 64, fb);
              tma_load_2d(sbb + (2 * b + 1) * 8192, &tmB1, col + b * 64, kb * 64, fb);
            }
          } else {
#pragma unroll
            for (int b = 0; b < BN / 64; b++) tma_load_2d(sbb + b * 8192, mp, col + b * 64, kb * 64, fb);
          }
          if (++st == C::STAGES) { st = 0; ph ^= 1; }
        }
      }
    }
    if (MC) asm volatile("barrier.cluster.arrive;\nbarrier.cluster.wait;" ::: "memory");
    return;
  }
  if (RC > 1) asm volatile("setmaxnreg.inc.sync.aligned.u32 %0;" ::"n"(RC > 1 ? RC : 24));
  const int wg = warp >> 2;
  float acc[BN / 2];
  int st = 0; uint32_t ph = 0;
  const uint32_t stg = sb + C::STG_OFF + warp * STGW;
  int pend = -1;
  auto publish = [&]() {
    if (pend >= 0 && lane == 0) {
      bulk_wait0();
      fence_async_all();
      red_release_add(&g_kvflag[pend], 1u);
      if (BN == 256) red_release_add(&g_kvflag[pend + 1], 1u);
    }
    pend = -1;
  };
  auto release = [&](int s) {
    if (MC) { if (lane < 2) mbar_arrive_cluster(mapa(empty0 + 8 * s, lane)); }
    else if (lane == 0) mbar_arrive(empty0 + 8 * s);
  };
  for (int t = t0; t < ntiles; t += tstep) {
    int mt, nt; tile_coords(p, t, mt, nt);
    if (MC) mt = 2 * mt + crank;
    int prev = -1;
    const int nkb = EPI == EPI_PART ? (nt < 5 ? 22 : 21) : p.kblocks;
    for (int kb = 0; kb < nkb; kb++) {
      mbar_wait(full0 + 8 * st, ph);
      const uint32_t sa = sb + st * C::STAGE + wg * 8192, sbb = sb + st * C::STAGE + C::A_BYTES;
      const uint64_t da = (uint64_t)((sa & 0x3FFFF) >> 4) | ((uint64_t)1 << 16) | ((uint64_t)(1024 >> 4) << 32) | ((uint64_t)1 << 62);
      const uint64_t db = (uint64_t)((sbb & 0x3FFFF) >> 4) | ((uint64_t)(8192 >> 4) << 16) | ((uint64_t)(1024 >> 4) << 32) | ((uint64_t)1 << 62);
      wg_fence();
#pragma unroll
      for (int k = 0; k < 4; k++) {
        if (BN == 256) wgmma_n256(acc, da + (uint64_t)(k * 2), db + (uint64_t)(k * 128), (kb | k) != 0);
        else wgmma_n128(acc, da + (uint64_t)(k * 2), db + (uint64_t)(k * 128), (kb | k) != 0);
      }
      wg_commit();
      if (prev >= 0) { wg_wait<1>(); release(prev); }
      prev = st;
      if (++st == C::STAGES) { st = 0; ph ^= 1; }
    }
    wg_wait<0>();
    release(prev);
    if (EPI == EPI_QKV) publish();
    const int row0 = mt * BM + warp * 16;
    const int srow = ((lane >> 3) & 1) * 8 + (lane & 7);
    const int schunk = lane >> 4;
    if (EPI == EPI_QKV) {
      const int gn = (nt + p.n_off) * BN, mat = gn / HD, head0 = (gn % HD) / DH;
      bf16* dstb = mat == 0 ? g_q : (mat == 1 ? g_k : g_v);
      if (lane == 0) bulk_wait_read0();
      __syncwarp();
#pragma unroll
      for (int hh = 0; hh < BN / 128; hh++) {
#pragma unroll
        for (int j = 0; j < 16; j += 2) {
          const float* a = acc + hh * 64 + j * 4;
          stsm4(stg + hh * 4096 + srow * 256 + (((j + schunk) ^ (srow & 7)) << 4), pack2(a[0], a[1]), pack2(a[2], a[3]), pack2(a[4], a[5]), pack2(a[6], a[7]));
        }
        fence_async_smem();
        __syncwarp();
        if (lane == 0) { bulk_s2g(dstb + ((size_t)(head0 + hh) * S_TOK + row0) * DH, stg + hh * 4096, 4096); bulk_commit(); }
      }
      if (p.use_flags) {
        pend = mt * 96 + nt * (BN / 128);
        if (t < t0 + 2 * tstep) publish();
      }
    } else if (EPI == EPI_PART) {
      float* dst = g_wpart + ((size_t)(nt / 5) * S_TOK + row0 + (lane >> 2)) * DM + (nt % 5) * BN + (lane & 3) * 2;
#pragma unroll
      for (int j = 0; j < BN / 8; j++) {
        *reinterpret_cast<float2*>(dst + j * 8) = make_float2(acc[j * 4], acc[j * 4 + 1]);
        *reinterpret_cast<float2*>(dst + 8 * DM + j * 8) = make_float2(acc[j * 4 + 2], acc[j * 4 + 3]);
      }
    } else if (EPI == EPI_RES) {
#pragma unroll
      for (int hh = 0; hh < BN / 128; hh++) {
        __syncwarp();
#pragma unroll
        for (int j = 0; j < 16; j += 2) {
          const float* a = acc + hh * 64 + j * 4;
          stsm4(stg + srow * 256 + (((j + schunk) ^ (srow & 7)) << 4), pack2(a[0], a[1]), pack2(a[2], a[3]), pack2(a[4], a[5]), pack2(a[6], a[7]));
        }
        __syncwarp();
        const int ch = lane & 15, col = nt * BN + hh * 128 + ch * 8;
        const float4 g0 = *reinterpret_cast<const float4*>(g_mod + p.gate_off + col);
        const float4 g1 = *reinterpret_cast<const float4*>(g_mod + p.gate_off + col + 4);
#pragma unroll
        for (int i = 0; i < 8; i++) {
          const int r = i * 2 + (lane >> 4);
          uint4 a = lds128(stg + r * 256 + ((ch ^ (r & 7)) << 4));
          uint4 x = *reinterpret_cast<const uint4*>(p.res + (size_t)(row0 + r) * DM + col);
          uint4 o;
          o.x = pack2(lo2f(x.x) + bfr(g0.x * lo2f(a.x)), hi2f(x.x) + bfr(g0.y * hi2f(a.x)));
          o.y = pack2(lo2f(x.y) + bfr(g0.z * lo2f(a.y)), hi2f(x.y) + bfr(g0.w * hi2f(a.y)));
          o.z = pack2(lo2f(x.z) + bfr(g1.x * lo2f(a.z)), hi2f(x.z) + bfr(g1.y * hi2f(a.z)));
          o.w = pack2(lo2f(x.w) + bfr(g1.z * lo2f(a.w)), hi2f(x.w) + bfr(g1.w * hi2f(a.w)));
          *reinterpret_cast<uint4*>(p.out + (size_t)(row0 + r) * DM + col) = o;
        }
      }
    } else {
#pragma unroll
      for (int hh = 0; hh < BN / 128; hh++) {
        __syncwarp();
#pragma unroll
        for (int j = 0; j < 8; j += 2) {
          const float* g = acc + hh * 64 + j * 4;
          const float* u = g + 32;
          uint32_t r[4];
#pragma unroll
          for (int e = 0; e < 4; e++) {
            const uint32_t gp = pack2(g[2 * e], g[2 * e + 1]), up = pack2(u[2 * e], u[2 * e + 1]);
            const uint32_t ap = pack2(gelu_tanh(lo2f(gp)), gelu_tanh(hi2f(gp)));
            r[e] = pack2(lo2f(ap) * lo2f(up), hi2f(ap) * hi2f(up));
          }
          stsm4(stg + srow * 128 + (((j + schunk) ^ (srow & 7)) << 4), r[0], r[1], r[2], r[3]);
        }
        __syncwarp();
        const int ch = lane & 7, col = nt * (BN / 2) + hh * 64 + ch * 8;
#pragma unroll
        for (int i = 0; i < 4; i++) {
          const int r = i * 4 + (lane >> 3);
          uint4 a = lds128(stg + r * 128 + ((ch ^ (r & 7)) << 4));
          *reinterpret_cast<uint4*>(g_act + (size_t)(row0 + r) * FF + col) = a;
        }
      }
    }
  }
  if (EPI == EPI_QKV) { publish(); if (lane == 0) bulk_wait0(); }
  if (MC) asm volatile("barrier.cluster.arrive;\nbarrier.cluster.wait;" ::: "memory");
  TL_END(tlid);
}

__global__ void gate_kernel(unsigned target) {
  for (int i = 0; i < 20000 && ld_acquire32(&g_resident2) < target; i++) __nanosleep(200);
}
#define PROF(i)
#define DELAY_A 850
#define DELAY_B 2300
#define ADAPT 0
#define AD_UP 100
#define AD_DN 10
#define WO_LATE 0
#define WO_AUX 0
namespace rc {
constexpr int OFF_VW = 0;
constexpr int OFF_WO = OFF_VW + 40960;
constexpr int OFF_K = OFF_WO + 57344;
constexpr int OFF_V = OFF_K + 16384;
constexpr int OFF_RED = OFF_V + 16384;
constexpr int OFF_B = OFF_RED + 16384;
constexpr int OFF_S = OFF_B + 10240;
constexpr int OFF_VM = OFF_S + 3840;
constexpr int OFF_F = OFF_VM + 2048;
constexpr int OFF_O = OFF_F + 2048;
constexpr int OFF_BAR = OFF_O + 2048;
constexpr int OFF_STG = OFF_K;
constexpr int SMEM = OFF_BAR + 128;
constexpr int NCTA = 96;
}
__device__ __forceinline__ float ex2(float x) { float y; asm("ex2.approx.ftz.f32 %0, %1;" : "=f"(y) : "f"(x)); return y; }
__device__ __forceinline__ void bar_arrive(int id, int n) { asm volatile("bar.arrive %0, %1;" ::"r"(id), "r"(n) : "memory"); }

__global__ void __cluster_dims__(3, 1, 1) __launch_bounds__(384, 1)
rec_kernel(const bf16* __restrict__ Wq, const bf16* __restrict__ Wk, const bf16* __restrict__ Wv, const bf16* __restrict__ Wo,
           const bf16* __restrict__ mem0) {
  using namespace rc;
  extern __shared__ __align__(1024) uint8_t smem_raw[];
  const uint32_t sb = smem_u32(smem_raw);
  const int tid = threadIdx.x, warp = tid >> 5, lane = tid & 31;
  const int head = blockIdx.x / 3, rank = blockIdx.x % 3;
  const int rho = lane >> 2, jj = lane & 3;
  const int kap = (lane >> 4) * 8 + (lane & 7);
  const int dhalf = (lane >> 3) & 1;
  const uint32_t bar_kv = sb + OFF_BAR, bar_xs = bar_kv + 16, bar_xv = bar_kv + 24;
  const int wt0 = rank * 13, wnt = rank == 2 ? 14 : 13;
  const int nqk = rank == 2 ? 2 : 3;
  TL_START(3);
  if (tid == 0) {
    atomicAdd(&g_resident, 1u);
    mbar_init(bar_kv, 1); mbar_init(bar_kv + 8, 1); mbar_init(bar_xs, 1); mbar_init(bar_xv, 1);
    asm volatile("fence.mbarrier_init.release.cluster;" ::: "memory");
  }
  asm volatile("barrier.cluster.arrive.aligned;\nbarrier.cluster.wait.aligned;" ::: "memory");

  if (warp < 8) {
    asm volatile("setmaxnreg.inc.sync.aligned.u32 208;");
    const int mg = warp >> 2, kq = warp & 3;
    auto tile_src = [&](int i) -> const bf16* {
      if (rank < 2) {
        if (i < 3) return Wq + head * DH + 48 * rank + 16 * i;
        if (i < 6) return Wk + head * DH + 48 * rank + 16 * (i - 3);
        return Wv + head * DH + 16 * (2 * rank + (i - 6));
      } else {
        if (i < 2) return Wq + head * DH + 96 + 16 * i;
        if (i == 2) return Wv + head * DH + 64;
        if (i < 5) return Wk + head * DH + 96 + 16 * (i - 3);
        if (i == 5) return Wv + head * DH + 80;
        return Wv + head * DH + 96 + 16 * (i - 6);
      }
    };
    const int kcol0 = 16 * ((kap & 7) >> 2) + 4 * (((kap & 7) >> 1) & 1) + (kap >> 3) + 8 * (kap & 1);
    uint32_t wa[3][10][4];
    const uint32_t lofs = (kq * 160 + kcol0) * 32 + dhalf * 16;
    auto stage_tile = [&](int i, uint32_t dst) {
      const bf16* src = tile_src(i);
      for (int e = tid; e < 1280; e += 256) {
        const int r = e >> 1, hf = e & 1;
        cp_async16(dst + r * 32 + hf * 16, src + (size_t)r * HD + hf * 8);
      }
    };
    for (int ti = 0; ti < 3; ti++) { stage_tile(ti, sb + OFF_STG + ti * 20480); stage_tile(3 + ti, sb + OFF_VW + ti * 20480); }
    cp_async_wait_all();
    bar_sync(9, 256);
    {
      const uint32_t lrow = sb + (mg ? OFF_VW : OFF_STG) + lofs + (mg ? 3 * 32 * 32 : 0);
#pragma unroll
      for (int ti = 0; ti < 3; ti++)
#pragma unroll
        for (int j = 0; j < 10; j++)
          ldsm4t(wa[ti][j], lrow + ti * 20480 + ((j >> 1) * 32 + (j & 1) * 2) * 32 - ((j >= 4 && mg) ? 5 * 32 * 32 : 0));
    }
    bar_sync(9, 256);
    stage_tile(6, sb + OFF_WO); stage_tile(7, sb + OFF_WO + 20480);
    {
      const int cpr = wnt * 2;
      for (int e = tid; e < 128 * cpr; e += 256) {
        const int r = e / cpr, c = e % cpr;
        cp_async16(sb + OFF_STG + r * 464 + c * 16, Wo + (size_t)(head * DH + r) * DM + wt0 * 16 + c * 8);
      }
    }
    cp_async_wait_all();
    bar_sync(9, 256);
#pragma unroll
    for (int ks = 0; ks < 10; ks++) {
      uint32_t r[4];
      ldsm4t(r, sb + OFF_WO + lofs + mg * 20480 + ((ks >> 1) * 32 + (ks & 1) * 2) * 32);
      sts128(sb + OFF_VW + (mg * 40 + kq * 10 + ks) * 512 + lane * 16, r[0], r[1], r[2], r[3]);
    }
    bar_sync(9, 256);
    for (int t = 0; t < wnt; t++) {
      uint32_t r[4];
      ldsm4t(r, sb + OFF_STG + (warp * 16 + kap) * 464 + t * 32 + dhalf * 16);
      sts128(sb + OFF_WO + (t * 8 + warp) * 512 + lane * 16, r[0], r[1], r[2], r[3]);
    }
    fence_async_smem();
    bar_sync(10, 384);
    uint32_t t_pub = (uint32_t)clock() - DELAY_B;
    int dly = DELAY_B;
    const uint32_t vb = sb + OFF_VW + (mg * 40 + kq * 10) * 512 + lane * 16;
    float* const part_dst = g_part + ((((size_t)(wt0 + warp) * 4 + jj) * 32 + head) * 8 + rho) * 4;
    const bool two = !WO_AUX && warp < wnt - 8;
    const int ttype = rank < 2 ? (warp < 3 ? 0 : (warp < 6 ? 1 : 2)) : ((warp == 2 || warp >= 5) ? 2 : (warp < 2 ? 0 : 1));
    const int vt = rank < 2 ? 2 * rank + (warp - 6) : (warp == 2 ? 4 : (warp == 5 ? 5 : warp));

    for (int s = 0; s < NSEG; s++) {
      const uint32_t par = s & 1;
      const bool last = s == NSEG - 1;
      PROF(0);
      uint4 va[10];
#pragma unroll
      for (int j = 0; j < 10; j++) va[j] = lds128(vb + (j < 4 ? j * 512 + mg * 3072 : j * 512 - mg * 2048));
      {
        const uint4* src = reinterpret_cast<const uint4*>(g_memb) + (s & 3) * 640 + (kq * 5 + mg * 3) * 32 + lane;
        while ((int)((uint32_t)clock() - t_pub) < dly) { }
#define BAD4(a) (a.x == ~0u || a.y == ~0u || a.z == ~0u || a.w == ~0u)
        uint4 x0 = ldg_relaxed128(src), x1 = ldg_relaxed128(src + 32), x2 = make_uint4(0, 0, 0, 0);
        if (mg == 0) x2 = ldg_relaxed128(src + 64);
        int guard = 0;
        while (true) {
          const bool b0 = BAD4(x0), b1 = BAD4(x1), b2 = BAD4(x2);
          if (!__any_sync(~0u, b0 || b1 || b2)) break;
          if (b0) x0 = ldg_relaxed128(src);
          if (b1) x1 = ldg_relaxed128(src + 32);
          if (b2) x2 = ldg_relaxed128(src + 64);
          if (++guard > (1 << 22)) { g_err = 3; __trap(); }
        }
        const uint32_t bb = sb + OFF_B + (kq * 5 + mg * 3) * 512 + lane * 16;
        sts128(bb, x0.x, x0.y, x0.z, x0.w); sts128(bb + 512, x1.x, x1.y, x1.z, x1.w);
        if (mg == 0) sts128(bb + 1024, x2.x, x2.y, x2.z, x2.w);
        bar_arrive((mg ? 12 : 1) + kq, 64);
        PROF(1);
        float c[4][4];
#pragma unroll
        for (int ti = 0; ti < 4; ti++) c[ti][0] = c[ti][1] = c[ti][2] = c[ti][3] = 0.f;
#pragma unroll
        for (int j = 0; j < 4; j++) {
          const uint4 x = j < 2 ? x0 : x1;
          const uint32_t b0 = (j & 1) ? x.z : x.x, b1 = (j & 1) ? x.w : x.y;
#pragma unroll
          for (int ti = 0; ti < 3; ti++) mma16816(c[ti], wa[ti][j][0], wa[ti][j][1], wa[ti][j][2], wa[ti][j][3], b0, b1);
          mma16816(c[3], va[j].x, va[j].y, va[j].z, va[j].w, b0, b1);
        }
        bar_sync((mg ? 1 : 12) + kq, 64);
        const uint32_t br = sb + OFF_B + (kq * 5 + (mg ? 0 : 2)) * 512 + lane * 16;
        uint4 bf[3];
#pragma unroll
        for (int kk = 0; kk < 3; kk++) bf[kk] = lds128(br + kk * 512);
#pragma unroll
        for (int j = 4; j < 10; j++) {
          const uint32_t b0 = (j & 1) ? bf[(j - 4) >> 1].z : bf[(j - 4) >> 1].x, b1 = (j & 1) ? bf[(j - 4) >> 1].w : bf[(j - 4) >> 1].y;
#pragma unroll
          for (int ti = 0; ti < 3; ti++) mma16816(c[ti], wa[ti][j][0], wa[ti][j][1], wa[ti][j][2], wa[ti][j][3], b0, b1);
          mma16816(c[3], va[j].x, va[j].y, va[j].z, va[j].w, b0, b1);
        }
#pragma unroll
        for (int ti = 0; ti < 3; ti++) sts128f(sb + OFF_RED + ((mg * 3 + ti) * 4 + kq) * 512 + lane * 16, c[ti]);
        sts128f(sb + OFF_RED + ((6 + mg) * 4 + kq) * 512 + lane * 16, c[3]);
      }
      PROF(2);
      bar_sync(5, 256);
      {
        const uint32_t ra = sb + OFF_RED + warp * 2048 + lane * 16;
        float4 q0 = lds128f(ra), q1 = lds128f(ra + 512), q2 = lds128f(ra + 1024), q3 = lds128f(ra + 1536);
        const uint32_t a0 = pack2((q0.x + q1.x) + (q2.x + q3.x), (q0.y + q1.y) + (q2.y + q3.y));
        const uint32_t a1 = pack2((q0.z + q1.z) + (q2.z + q3.z), (q0.w + q1.w) + (q2.w + q3.w));
        if (ttype == 2 && !last) {
#pragma unroll
          for (int r = 0; r < 3; r++) st_async64(mapa(sb + OFF_VM + vt * 256 + lane * 8, r), a0, a1, mapa(bar_xv, r));
        }
        const uint32_t f0 = movtrans(a0), f1 = movtrans(a1);
        if (ttype < 2) sts64(sb + OFF_F + warp * 256 + lane * 8, f0, f1);
        if (warp == 1) {
          bar_sync(6, 384);
          if (!last) {
            float sm[2][4];
            uint2 qa[3], kk[3];
#pragma unroll
            for (int i = 0; i < 3; i++) {
              qa[i] = make_uint2(0u, 0u); kk[i] = make_uint2(0u, 0u);
              if (i < nqk) { qa[i] = lds64(sb + OFF_F + i * 256 + lane * 8); kk[i] = lds64(sb + OFF_F + (3 + i) * 256 + lane * 8); }
            }
#pragma unroll
            for (int i = 0; i < 2; i++) sm[i][0] = sm[i][1] = sm[i][2] = sm[i][3] = 0.f;
#pragma unroll
            for (int i = 0; i < 3; i++) mma16816(sm[i & 1], qa[i].x, 0u, qa[i].y, 0u, kk[i].x, kk[i].y);
            const uint32_t m0 = __float_as_uint(sm[0][0] + sm[1][0]), m1 = __float_as_uint(sm[0][1] + sm[1][1]);
#pragma unroll
            for (int r = 0; r < 3; r++) st_async64(mapa(sb + OFF_S + rank * 1280 + 1024 + lane * 8, r), m0, m1, mapa(bar_xs, r));
          }
        } else {
          bar_arrive(6, 384);
        }
        PROF(3);
        if (ttype) {
          const int c0 = ttype == 1 ? rank * 6 + 2 * (warp - 3) : 2 * vt;
          uint32_t* dst = reinterpret_cast<uint32_t*>((ttype == 1 ? g_km : g_vm) + ((size_t)(s * NH + head) * NMEM + rho) * DH);
          dst[((c0 ^ rho) << 2) + jj] = f0;
          dst[(((c0 + 1) ^ rho) << 2) + jj] = f1;
        }
      }
      if (last) break;
      uint4 p0[8], p1[8];
#pragma unroll
      for (int ks = 0; ks < 8; ks++) p0[ks] = lds128(sb + OFF_WO + (warp * 8 + ks) * 512 + lane * 16);
#pragma unroll
      for (int ks = 0; ks < 8; ks++) p1[ks] = lds128(sb + OFF_WO + ((two ? 8 + warp : warp) * 8 + ks) * 512 + lane * 16);
      PROF(8);
      bar_sync(8, 384);
      const uint32_t flag = ((s >> 1) & 1) ^ 1;
      {
        float c[4][4];
#pragma unroll
        for (int a = 0; a < 4; a++) c[a][0] = c[a][1] = c[a][2] = c[a][3] = 0.f;
        uint4 ob[4];
#pragma unroll
        for (int i = 0; i < 4; i++) ob[i] = lds128(sb + OFF_O + i * 512 + lane * 16);
#pragma unroll
        for (int i = 0; i < 4; i++) {
          mma16816(c[0], p0[2 * i].x, p0[2 * i].y, p0[2 * i].z, p0[2 * i].w, ob[i].x, ob[i].y);
          mma16816(c[1], p0[2 * i + 1].x, p0[2 * i + 1].y, p0[2 * i + 1].z, p0[2 * i + 1].w, ob[i].z, ob[i].w);
          mma16816(c[2], p1[2 * i].x, p1[2 * i].y, p1[2 * i].z, p1[2 * i].w, ob[i].x, ob[i].y);
          mma16816(c[3], p1[2 * i + 1].x, p1[2 * i + 1].y, p1[2 * i + 1].z, p1[2 * i + 1].w, ob[i].z, ob[i].w);
        }
        float* dst0 = part_dst + (size_t)par * (160 * 32 * 8 * 4);
#pragma unroll
        for (int a = 0; a < 2; a++) {
          if (a == 0 || two) {
            uint32_t w[4];
#pragma unroll
            for (int e = 0; e < 4; e++) w[e] = (__float_as_uint(c[2 * a][e] + c[2 * a + 1][e]) & ~1u) | flag;
            stg_relaxed128(dst0 + a * (8 * 4 * 32 * 8 * 4), w[0], w[1], w[2], w[3]);
          }
        }
      }
      t_pub = (uint32_t)clock();
      PROF(9);
    }
  } else {
    asm volatile("setmaxnreg.dec.sync.aligned.u32 88;");
    const int aw = warp - 8;
    const bf16* kbase = g_k + (size_t)head * S_TOK * DH;
    const bf16* vbase = g_v + (size_t)head * S_TOK * DH;
    {
      const int gt = blockIdx.x * 128 + (tid - 256), GT = NCTA * 128;
      uint4* pp = reinterpret_cast<uint4*>(g_part);
      for (int i = gt; i < 2 * 160 * 32 * 8; i += GT) pp[i] = make_uint4(0, 0, 0, 0);
      uint4* pm = reinterpret_cast<uint4*>(g_memb);
      for (int i = gt + 640; i < 4 * 640; i += GT) pm[i] = make_uint4(~0u, ~0u, ~0u, ~0u);
      if (gt < 2560) {
        const int i = gt & 3, l = (gt >> 2) & 31, kk = gt >> 7;
        const int n = l >> 2, u = 4 * kk + (l & 3), col = 16 * (u >> 1) + 4 * (u & 1) + i;
        const uint32_t lo = reinterpret_cast<const unsigned short*>(mem0)[n * DM + col];
        const uint32_t hi = reinterpret_cast<const unsigned short*>(mem0)[n * DM + col + 8];
        uint32_t wv = lo | (hi << 16);
        if (wv == 0xffffffffu) wv = 0x7fff7fffu;
        g_memb[gt] = wv;
      }
      __threadfence();
      bar_sync(11, 128);
      if (aw == 0 && lane == 0) {
        atomicAdd(&g_ready, 1u);
        int guard = 0;
        while (ld_acquire32(&g_ready) < (unsigned)NCTA) { __nanosleep(200); if (++guard > (1 << 22)) { g_err = 8; __trap(); } }
      }
    }
    auto load_kv = [&](int sg) {
      if ((sg & 3) == 0) {
        const unsigned* f = g_kvflag + (sg >> 2) * 96 + 32 + head;
        int guard = 0;
        while (ld_acquire32(f) < 8u || ld_acquire32(f + 32) < 8u) { __nanosleep(100); if (++guard > (1 << 22)) { g_err = 5; __trap(); } }
        fence_async_all();
      }
      const int b = sg & 1;
      mbar_expect_tx(bar_kv + 8 * b, 16384);
      bulk_g2s(sb + OFF_K + b * 8192, kbase + (size_t)sg * SEG * DH, 8192, bar_kv + 8 * b);
      bulk_g2s(sb + OFF_V + b * 8192, vbase + (size_t)sg * SEG * DH, 8192, bar_kv + 8 * b);
    };
    bar_sync(10, 384);
    if (aw == 1 && lane == 0) { load_kv(0); load_kv(1); }
    __syncwarp();
    uint32_t xs_dst[3], xs_bar[3];
#pragma unroll
    for (int r = 0; r < 3; r++) { xs_dst[r] = mapa(sb + OFF_S + rank * 1280 + aw * 256 + lane * 8, r); xs_bar[r] = mapa(bar_xs, r); }
    const int unit = (3 - aw) * NCTA + blockIdx.x;
    const bool is_red = unit < 160;
    int dly = DELAY_A + 300;
    for (int s = 0; s < NSEG - 1; s++) {
      const uint32_t par = s & 1;
      if (aw == 0 && lane == 0) { mbar_expect_tx(bar_xs, 3840); mbar_expect_tx(bar_xv, 2048); }
      PROF(0);
      uint32_t kf[3][2], va[2][2][4];
      mbar_wait(bar_kv + 8 * par, (s >> 1) & 1);
      {
        const int key = aw * 8 + (lane & 7);
#pragma unroll
        for (int i = 0; i < 3; i++) {
          const int ch = rank * 6 + 2 * i + dhalf;
          if (i < nqk) ldsm2(kf[i], sb + OFF_K + par * 8192 + key * 256 + ((ch ^ (key & 7)) << 4));
          else kf[i][0] = kf[i][1] = 0u;
        }
#pragma unroll
        for (int m = 0; m < 2; m++)
#pragma unroll
          for (int ks = 0; ks < 2; ks++) {
            const int k2 = ks * 16 + kap, ch = 2 * (aw + 4 * m) + dhalf;
            ldsm4t(va[m][ks], sb + OFF_V + par * 8192 + k2 * 256 + ((ch ^ (k2 & 7)) << 4));
          }
      }
      PROF(1);
      bar_sync(6, 384);
      {
        float sc[2][4];
        uint2 qa[3];
#pragma unroll
        for (int i = 0; i < 3; i++) {
          qa[i] = make_uint2(0u, 0u);
          if (i < nqk) qa[i] = lds64(sb + OFF_F + i * 256 + lane * 8);
        }
#pragma unroll
        for (int i = 0; i < 2; i++) sc[i][0] = sc[i][1] = sc[i][2] = sc[i][3] = 0.f;
#pragma unroll
        for (int i = 0; i < 3; i++) mma16816(sc[i & 1], qa[i].x, 0u, qa[i].y, 0u, kf[i][0], kf[i][1]);
        const uint32_t s0 = __float_as_uint(sc[0][0] + sc[1][0]), s1 = __float_as_uint(sc[0][1] + sc[1][1]);
#pragma unroll
        for (int r = 0; r < 3; r++) st_async64(xs_dst[r], s0, s1, xs_bar[r]);
      }
      PROF(4);
      mbar_wait(bar_xs, par);
      PROF(6);
      float v[10];
      {
        const uint32_t sa = sb + OFF_S + lane * 8;
#pragma unroll
        for (int n = 0; n < 5; n++) {
          const uint2 a = lds64(sa + n * 256), b = lds64(sa + 1280 + n * 256), c = lds64(sa + 2560 + n * 256);
          v[2 * n] = __uint_as_float(a.x) + __uint_as_float(b.x) + __uint_as_float(c.x);
          v[2 * n + 1] = __uint_as_float(a.y) + __uint_as_float(b.y) + __uint_as_float(c.y);
        }
      }
      float mx = fmaxf(fmaxf(fmaxf(v[0], v[1]), fmaxf(v[2], v[3])), fmaxf(fmaxf(v[4], v[5]), fmaxf(v[6], v[7])));
      mx = fmaxf(mx, fmaxf(v[8], v[9]));
      mx = fmaxf(mx, __shfl_xor_sync(~0u, mx, 1));
      mx = fmaxf(mx, __shfl_xor_sync(~0u, mx, 2));
      const float kscale = 0.08838834764831845f * 1.4426950408889634f;
      const float mo = -mx * kscale;
#pragma unroll
      for (int i = 0; i < 10; i++) v[i] = ex2(fmaf(v[i], kscale, mo));
      const uint32_t p0 = pack2(v[0], v[1]), p1 = pack2(v[2], v[3]), p2 = pack2(v[4], v[5]), p3 = pack2(v[6], v[7]), p4 = pack2(v[8], v[9]);
      PROF(7);
      {
        float c[2][4], d[2][4];
#pragma unroll
        for (int m = 0; m < 2; m++) {
          c[m][0] = c[m][1] = c[m][2] = c[m][3] = 0.f; d[m][0] = d[m][1] = d[m][2] = d[m][3] = 0.f;
          mma16816(c[m], va[m][0][0], va[m][0][1], va[m][0][2], va[m][0][3], p0, p1);
          mma16816(d[m], va[m][1][0], va[m][1][1], va[m][1][2], va[m][1][3], p2, p3);
        }
        mbar_wait(bar_xv, par);
        uint2 vm[2];
#pragma unroll
        for (int m = 0; m < 2; m++) vm[m] = lds64(sb + OFF_VM + (aw + 4 * m) * 256 + lane * 8);
#pragma unroll
        for (int m = 0; m < 2; m++) mma16816(d[m], vm[m].x, vm[m].y, 0u, 0u, p4, 0u);
        float sum = ((lo2f(p0) + hi2f(p0)) + (lo2f(p1) + hi2f(p1))) + ((lo2f(p2) + hi2f(p2)) + (lo2f(p3) + hi2f(p3))) + (lo2f(p4) + hi2f(p4));
        sum += __shfl_xor_sync(~0u, sum, 1);
        sum += __shfl_xor_sync(~0u, sum, 2);
        const float inv = __fdividef(1.f, sum);
        const float i0 = __shfl_sync(~0u, inv, jj * 8), i1 = __shfl_sync(~0u, inv, jj * 8 + 4);
#pragma unroll
        for (int m = 0; m < 2; m++) {
          const int mt = aw + 4 * m;
          const uint32_t b0 = movtrans(pack2((c[m][0] + d[m][0]) * i0, (c[m][1] + d[m][1]) * i1));
          const uint32_t b1 = movtrans(pack2((c[m][2] + d[m][2]) * i0, (c[m][3] + d[m][3]) * i1));
          sts64(sb + OFF_O + (mt >> 1) * 512 + lane * 16 + (mt & 1) * 8, b0, b1);
        }
      }
      PROF(8);
      bar_sync(8, 384);
      const uint32_t flag = ((s >> 1) & 1) ^ 1;
      const uint32_t t_o = (uint32_t)clock();
      PROF(9);
      if (aw == 1 && lane == 0) {
        __threadfence();
        atomicAdd(&g_mflag[s * NH + head], 1u);
        if (s + 2 < NSEG - 1) load_kv(s + 2);
      }
      if (is_red) {
        const uint4* src = reinterpret_cast<const uint4*>(g_part) + ((size_t)par * 160 + unit) * 256 + lane;
        uint4 w[8];
        int guard = 0;
        while ((int)((uint32_t)clock() - t_o) < dly) { }
#pragma unroll
        for (int i = 0; i < 8; i++) w[i] = ldg_relaxed128(src + i * 32);
        const uint32_t fx = flag ? 0u : 1u;
        while (true) {
          uint32_t bad = 0;
#pragma unroll
          for (int i = 0; i < 8; i++) bad |= (~((w[i].x ^ fx) & (w[i].y ^ fx) & (w[i].z ^ fx) & (w[i].w ^ fx)) & 1u) << i;
          if (!__any_sync(~0u, bad != 0)) break;
#pragma unroll
          for (int i = 0; i < 8; i++) if (bad & (1u << i)) w[i] = ldg_relaxed128(src + i * 32);
          if (++guard > (1 << 22)) { g_err = 4; __trap(); }
        }
        PROF(10);
#define F_(i, m) __uint_as_float(w[i].m)
        float r0 = ((F_(0, x) + F_(1, x)) + (F_(2, x) + F_(3, x))) + ((F_(4, x) + F_(5, x)) + (F_(6, x) + F_(7, x)));
        float r1 = ((F_(0, y) + F_(1, y)) + (F_(2, y) + F_(3, y))) + ((F_(4, y) + F_(5, y)) + (F_(6, y) + F_(7, y)));
        float r2 = ((F_(0, z) + F_(1, z)) + (F_(2, z) + F_(3, z))) + ((F_(4, z) + F_(5, z)) + (F_(6, z) + F_(7, z)));
        float r3 = ((F_(0, w) + F_(1, w)) + (F_(2, w) + F_(3, w))) + ((F_(4, w) + F_(5, w)) + (F_(6, w) + F_(7, w)));
#undef F_
#pragma unroll
        for (int o = 8; o < 32; o <<= 1) {
          r0 += __shfl_xor_sync(~0u, r0, o); r1 += __shfl_xor_sync(~0u, r1, o);
          r2 += __shfl_xor_sync(~0u, r2, o); r3 += __shfl_xor_sync(~0u, r3, o);
        }
        if (lane < 16) {
          const int t = unit >> 2, j = unit & 3, e = lane >> 3, r8 = lane & 7;
          const int w0 = ((t >> 1) * 32 + (2 * j + e) * 4 + (t & 1) * 2) * 4 + r8;
          stg_relaxed32(g_memb + ((s + 1) & 3) * 2560 + w0, e ? pack2(r1, r3) : pack2(r0, r2));
          stg_relaxed32(g_memb + ((s + 3) & 3) * 2560 + w0, ~0u);
        }
      }
    }
    bar_sync(6, 384);
  }
  asm volatile("barrier.cluster.arrive;\nbarrier.cluster.wait;" ::: "memory");
  if (tid == 0) { __threadfence(); atomicAdd(&g_mflag[(NSEG - 1) * NH + head], 1u); }
  TL_END(3);
}

#define ATT_SLEEP 400
constexpr int ATT_BUF = 8192 * 3 + 4096;
constexpr int ATT_SMEM = 2 * ATT_BUF + 64;
__global__ void __launch_bounds__(128, 4) attn_kernel(int seg0) {
  extern __shared__ __align__(1024) uint8_t smem_raw[];
  const int warp = threadIdx.x >> 5, lane = threadIdx.x & 31;
  const int pr = warp >> 1, wp = warp & 1;
  const uint32_t sb = smem_u32(smem_raw) + pr * ATT_BUF;
  const uint32_t sQ = sb, sK = sb + 8192, sV = sb + 16384, sKm = sb + 24576, sVm = sKm + 2048;
  const uint32_t bar = smem_u32(smem_raw) + 2 * ATT_BUF + pr * 8;
  const int head = blockIdx.x & 31;
  TL_START(4);
  if (threadIdx.x == 0) {
    mbar_init(bar, 2); mbar_init(bar + 8, 2);
    asm volatile("fence.mbarrier_init.release.cluster;" ::: "memory");
  }
  __syncthreads();
  for (int seg = seg0 + (blockIdx.x >> 5) * 2 + pr, it = 0; it < 1; it++) {
  if (wp == 0) {
    if (lane < 3) {
      const unsigned* fq = g_kvflag + (seg >> 2) * 96 + head + lane * 32;
      int guard = 0;
      while (ld_acquire32(fq) < 8u) { __nanosleep(1000); if (++guard > (1 << 21)) { g_err = 6; __trap(); } }
    }
    __syncwarp();
    if (lane == 0) {
      fence_async_all();
      mbar_expect_tx(bar, 8192 * 3);
      const size_t off = ((size_t)head * S_TOK + seg * SEG) * DH;
      bulk_g2s(sQ, g_q + off, 8192, bar); bulk_g2s(sK, g_k + off, 8192, bar); bulk_g2s(sV, g_v + off, 8192, bar);
    }
  } else if (lane == 0) {
    const unsigned* fm = g_mflag + seg * NH + head;
    int guard = 0;
    while (ld_acquire32(fm) < 3u) { __nanosleep(ATT_SLEEP); if (++guard > (1 << 22)) { g_err = 6; __trap(); } }
    fence_async_all();
    mbar_expect_tx(bar, 4096);
    const size_t offm = (size_t)(seg * NH + head) * NMEM * DH;
    bulk_g2s(sKm, g_km + offm, 2048, bar); bulk_g2s(sVm, g_vm + offm, 2048, bar);
  }
  __syncwarp();
  mbar_wait(bar, it & 1);
  const int rho = lane >> 2, jj = lane & 3;
  float sc[5][4];
#pragma unroll
  for (int n = 0; n < 5; n++) sc[n][0] = sc[n][1] = sc[n][2] = sc[n][3] = 0.f;
#pragma unroll
  for (int ks = 0; ks < 8; ks++) {
    uint32_t a[4];
    {
      const int row = wp * 16 + ((lane >> 3) & 1) * 8 + (lane & 7), ch = 2 * ks + (lane >> 4);
      ldsm4(a, sQ + row * 256 + ((ch ^ (row & 7)) << 4));
    }
#pragma unroll
    for (int n = 0; n < 4; n += 2) {
      uint32_t kf[4];
      const int key = (n + (lane >> 4)) * 8 + (lane & 7), ch = 2 * ks + ((lane >> 3) & 1);
      ldsm4(kf, sK + key * 256 + ((ch ^ (key & 7)) << 4));
      mma16816(sc[n], a[0], a[1], a[2], a[3], kf[0], kf[1]);
      mma16816(sc[n + 1], a[0], a[1], a[2], a[3], kf[2], kf[3]);
    }
    uint32_t mf[2];
    {
      const int key = lane & 7, ch = 2 * ks + ((lane >> 3) & 1);
      ldsm2(mf, sKm + key * 256 + ((ch ^ key) << 4));
    }
    mma16816(sc[4], a[0], a[1], a[2], a[3], mf[0], mf[1]);
  }
  uint32_t pa[3][4];
  {
    float mx0 = -3.0e38f, mx1 = -3.0e38f;
    const int q0 = wp * 16 + rho, q1 = q0 + 8;
#pragma unroll
    for (int n = 0; n < 5; n++) {
#pragma unroll
      for (int e = 0; e < 4; e++) {
        float v = bfr(bfr(sc[n][e]) * 0.08838834764831845f);
        if (n < 4) { const int key = n * 8 + jj * 2 + (e & 1); if (key > ((e & 2) ? q1 : q0)) v = -1.0e9f; }
        sc[n][e] = v;
        if (e & 2) mx1 = fmaxf(mx1, v); else mx0 = fmaxf(mx0, v);
      }
    }
    mx0 = fmaxf(mx0, __shfl_xor_sync(~0u, mx0, 1)); mx0 = fmaxf(mx0, __shfl_xor_sync(~0u, mx0, 2));
    mx1 = fmaxf(mx1, __shfl_xor_sync(~0u, mx1, 1)); mx1 = fmaxf(mx1, __shfl_xor_sync(~0u, mx1, 2));
    float s0 = 0.f, s1 = 0.f;
#pragma unroll
    for (int n = 0; n < 5; n++) {
      sc[n][0] = __expf(sc[n][0] - mx0); sc[n][1] = __expf(sc[n][1] - mx0); s0 += sc[n][0] + sc[n][1];
      sc[n][2] = __expf(sc[n][2] - mx1); sc[n][3] = __expf(sc[n][3] - mx1); s1 += sc[n][2] + sc[n][3];
    }
    s0 += __shfl_xor_sync(~0u, s0, 1); s0 += __shfl_xor_sync(~0u, s0, 2);
    s1 += __shfl_xor_sync(~0u, s1, 1); s1 += __shfl_xor_sync(~0u, s1, 2);
    const float i0 = 1.f / s0, i1 = 1.f / s1;
#pragma unroll
    for (int ks = 0; ks < 2; ks++) {
      pa[ks][0] = pack2(sc[2 * ks][0] * i0, sc[2 * ks][1] * i0); pa[ks][1] = pack2(sc[2 * ks][2] * i1, sc[2 * ks][3] * i1);
      pa[ks][2] = pack2(sc[2 * ks + 1][0] * i0, sc[2 * ks + 1][1] * i0); pa[ks][3] = pack2(sc[2 * ks + 1][2] * i1, sc[2 * ks + 1][3] * i1);
    }
    pa[2][0] = pack2(sc[4][0] * i0, sc[4][1] * i0); pa[2][1] = pack2(sc[4][2] * i1, sc[4][3] * i1); pa[2][2] = 0; pa[2][3] = 0;
  }
  __syncwarp();
  const int srow = ((lane >> 3) & 1) * 8 + (lane & 7), schunk = lane >> 4;
#pragma unroll
  for (int n = 0; n < 16; n += 2) {
    float o0[4] = {0.f, 0.f, 0.f, 0.f}, o1[4] = {0.f, 0.f, 0.f, 0.f};
#pragma unroll
    for (int ks = 0; ks < 2; ks++) {
      uint32_t vf[4];
      const int key = ks * 16 + ((lane >> 3) & 1) * 8 + (lane & 7), ch = n + (lane >> 4);
      ldsm4t(vf, sV + key * 256 + ((ch ^ (key & 7)) << 4));
      mma16816(o0, pa[ks][0], pa[ks][1], pa[ks][2], pa[ks][3], vf[0], vf[1]);
      mma16816(o1, pa[ks][0], pa[ks][1], pa[ks][2], pa[ks][3], vf[2], vf[3]);
    }
    uint32_t mf[2];
    {
      const int key = lane & 7, ch = n + ((lane >> 3) & 1);
      ldsm2t(mf, sVm + key * 256 + ((ch ^ key) << 4));
    }
    mma16816(o0, pa[2][0], pa[2][1], 0u, 0u, mf[0], 0u);
    mma16816(o1, pa[2][0], pa[2][1], 0u, 0u, mf[1], 0u);
    stsm4(sQ + (wp * 16 + srow) * 256 + (((n + schunk) ^ (srow & 7)) << 4), pack2(o0[0], o0[1]), pack2(o0[2], o0[3]), pack2(o1[0], o1[1]), pack2(o1[2], o1[3]));
  }
  __syncwarp();
#pragma unroll
  for (int i = 0; i < 8; i++) {
    const int r = i * 2 + (lane >> 4), ch = lane & 15;
    uint4 a = lds128(sQ + (wp * 16 + r) * 256 + ((ch ^ (r & 7)) << 4));
    *reinterpret_cast<uint4*>(g_o + (size_t)(seg * SEG + wp * 16 + r) * HD + head * DH + ch * 8) = a;
  }
  }
  TL_END(4);
}

__device__ float g_fb_mem[NMEM * DM], g_fb_q[NMEM * HD], g_fb_o[NMEM * HD];
__device__ __forceinline__ size_t swz(int row, int d) { return (size_t)row * DH + ((((d >> 3) ^ (row & 7)) << 3) | (d & 7)); }
__global__ void fb_init(const bf16* mem0) {
  for (int i = threadIdx.x; i < NMEM * DM; i += blockDim.x) g_fb_mem[i] = __bfloat162float(mem0[i]);
}
__global__ void __launch_bounds__(128) fb_qkv(const bf16* Wq, const bf16* Wk, const bf16* Wv, int s) {
  __shared__ float sm[NMEM * DM];
  for (int i = threadIdx.x; i < NMEM * DM; i += 128) sm[i] = g_fb_mem[i];
  __syncthreads();
  const int c = blockIdx.x * 128 + threadIdx.x, mat = c / HD, col = c % HD, head = col / DH, d = col % DH;
  const bf16* W = mat == 0 ? Wq : (mat == 1 ? Wk : Wv);
  float acc[NMEM];
  for (int r = 0; r < NMEM; r++) acc[r] = 0.f;
  for (int k = 0; k < DM; k++) {
    const float w = __bfloat162float(W[(size_t)k * HD + col]);
    for (int r = 0; r < NMEM; r++) acc[r] += sm[r * DM + k] * w;
  }
  for (int r = 0; r < NMEM; r++) {
    if (mat == 0) g_fb_q[r * HD + col] = bfr(acc[r]);
    else (mat == 1 ? g_km : g_vm)[(size_t)(s * NH + head) * NMEM * DH + swz(r, d)] = __float2bfloat16_rn(acc[r]);
  }
  if (threadIdx.x == 0 && blockIdx.x < NH) g_mflag[s * NH + blockIdx.x] = 3u;
}
__global__ void __launch_bounds__(128) fb_attn(int s) {
  __shared__ float p[NMEM][40];
  const int head = blockIdx.x, tid = threadIdx.x;
  const bf16* km = g_km + (size_t)(s * NH + head) * NMEM * DH;
  const bf16* vm = g_vm + (size_t)(s * NH + head) * NMEM * DH;
  const bf16* kt = g_k + ((size_t)head * S_TOK + s * SEG) * DH;
  const bf16* vt = g_v + ((size_t)head * S_TOK + s * SEG) * DH;
  for (int e = tid; e < NMEM * 40; e += 128) {
    const int r = e / 40, j = e % 40;
    float a = 0.f;
    for (int d = 0; d < DH; d++) a += g_fb_q[r * HD + head * DH + d] * __bfloat162float(j < NMEM ? km[swz(j, d)] : kt[swz(j - NMEM, d)]);
    p[r][j] = a * 0.08838834764831845f;
  }
  __syncthreads();
  if (tid < NMEM) {
    float mx = -3.0e38f, sum = 0.f;
    for (int j = 0; j < 40; j++) mx = fmaxf(mx, p[tid][j]);
    for (int j = 0; j < 40; j++) { p[tid][j] = __expf(p[tid][j] - mx); sum += p[tid][j]; }
    for (int j = 0; j < 40; j++) p[tid][j] = bfr(p[tid][j] / sum);
  }
  __syncthreads();
  for (int r = 0; r < NMEM; r++) {
    float a = 0.f;
    for (int j = 0; j < 40; j++) a += p[r][j] * __bfloat162float(j < NMEM ? vm[swz(j, tid)] : vt[swz(j - NMEM, tid)]);
    g_fb_o[r * HD + head * DH + tid] = bfr(a);
  }
}
__global__ void __launch_bounds__(256) fb_wo(const bf16* Wo) {
  __shared__ float red[8][NMEM][32];
  const int col = blockIdx.x * 32 + (threadIdx.x & 31), kg = threadIdx.x >> 5;
  float acc[NMEM];
  for (int r = 0; r < NMEM; r++) acc[r] = 0.f;
  for (int k = kg * 512; k < kg * 512 + 512; k++) {
    const float w = __bfloat162float(Wo[(size_t)k * DM + col]);
    for (int r = 0; r < NMEM; r++) acc[r] += g_fb_o[r * HD + k] * w;
  }
  for (int r = 0; r < NMEM; r++) red[kg][r][threadIdx.x & 31] = acc[r];
  __syncthreads();
  const int r = kg;
  float s = 0.f;
  for (int g = 0; g < 8; g++) s += red[g][r][threadIdx.x & 31];
  g_fb_mem[r * DM + col] = bfr(s);
}

typedef CUresult (*EncodeFn)(CUtensorMap*, CUtensorMapDataType, cuuint32_t, void*, const cuuint64_t*, const cuuint64_t*,
                             const cuuint32_t*, const cuuint32_t*, CUtensorMapInterleave, CUtensorMapSwizzle,
                             CUtensorMapL2promotion, CUtensorMapFloatOOBfill);
#define USE_PDL 1
#define MC_POST 0
#define MC_QKV 0
#define QKV_ST 3
#define GK_QKV gemm_kernel<256, EPI_QKV, QKV_ST, 288, 1, 0, 128, MC_QKV>
#define GK_RES gemm_kernel<128, EPI_RES, 4, 640, 1, 128>
#define GK_RESB gemm_kernel<128, EPI_RES, 5, 288, 1, 0, 128, MC_POST>
constexpr int SM_RESB = GemmCfg<128, 5>::SMEM;
#define GK_RES64 gemm_kernel<128, EPI_RES, 4, 160, 2, 0, 64>
constexpr int SM_RES64 = GemmCfg<128, 4, 4096, 64>::SMEM;
#define ATT_LSMEM ATT_SMEM
#define EARLY 0
#define WO64 0
#define WO_SPLIT 0
#define GK_PART gemm_kernel<128, EPI_PART, 6, 288, 1, 0>
constexpr int SM_PART = GemmCfg<128, 6, 2048>::SMEM;
#define WO_SPLITK 0
#define GK_GLU gemm_kernel<128, EPI_GEGLU, 3, 288, 2, 0, 128, MC_POST>
constexpr int SM_QKV = GemmCfg<256, QKV_ST, 8192>::SMEM, SM_RES = GemmCfg<128, 4>::SMEM, SM_GLU = GemmCfg<128, 3, 2048>::SMEM;
static EncodeFn s_encode = nullptr;
static int s_fallback = 0;
static cudaStream_t s_rec, s_att;
static cudaEvent_t s_evFork, s_evJoin, s_evFork2, s_evJoin2, s_evJoin3;
#define SHADOW_CTAS 34

static CUtensorMap make_map(const void* ptr, uint64_t inner, uint64_t outer, uint32_t box_inner, uint32_t box_outer, bool swz = true) {
  CUtensorMap m;
  cuuint64_t dims[2] = {inner, outer};
  cuuint64_t strides[1] = {inner * 2};
  cuuint32_t box[2] = {box_inner, box_outer};
  cuuint32_t es[2] = {1, 1};
  s_encode(&m, CU_TENSOR_MAP_DATA_TYPE_BFLOAT16, 2, const_cast<void*>(ptr), dims, strides, box, es, CU_TENSOR_MAP_INTERLEAVE_NONE,
           swz ? CU_TENSOR_MAP_SWIZZLE_128B : CU_TENSOR_MAP_SWIZZLE_NONE, CU_TENSOR_MAP_L2_PROMOTION_L2_256B, CU_TENSOR_MAP_FLOAT_OOB_FILL_NONE);
  return m;
}
template <class K>
static void launch_gemm(K kern, int grid, int block, int smem, cudaStream_t st, int mc, const CUtensorMap& a, const CUtensorMap& b0,
                        const CUtensorMap& b1, const CUtensorMap& b2, GemmP p, int pdl = 0) {
  if (mc) p.m_tiles /= 2;
  cudaLaunchConfig_t cfg = {};
  cfg.gridDim = dim3(grid); cfg.blockDim = dim3(block); cfg.dynamicSmemBytes = smem; cfg.stream = st;
  cudaLaunchAttribute at[2];
  at[0].id = cudaLaunchAttributeClusterDimension;
  at[0].val.clusterDim.x = mc ? 2 : 1; at[0].val.clusterDim.y = 1; at[0].val.clusterDim.z = 1;
  at[1].id = cudaLaunchAttributeProgrammaticStreamSerialization;
  at[1].val.programmaticStreamSerializationAllowed = 1;
  cfg.attrs = at; cfg.numAttrs = pdl ? 2 : 1;
  cudaLaunchKernelEx(&cfg, kern, a, b0, b1, b2, p);
}
template <class T> static void* sym_addr(T& sym) { void* p = nullptr; cudaGetSymbolAddress(&p, sym); return p; }

extern "C" void kernel_launch(void* const* d_in, const int* in_sizes, int n_in, void* d_out, int out_size) {
  const bf16* x = (const bf16*)d_in[0];
  const bf16* mem0 = (const bf16*)d_in[1];
  const bf16* Wq = (const bf16*)d_in[2];
  const bf16* Wk = (const bf16*)d_in[3];
  const bf16* Wv = (const bf16*)d_in[4];
  const bf16* Wo = (const bf16*)d_in[5];
  const bf16* w_gate = (const bf16*)d_in[8];
  const bf16* w_up = (const bf16*)d_in[9];
  const bf16* w_down = (const bf16*)d_in[10];
  const bf16* cvec = (const bf16*)d_in[11];
  const bf16* w_mod = (const bf16*)d_in[12];
  bf16* out = (bf16*)d_out;

  static bool init = false;
  static void *p_h, *p_o, *p_x1, *p_h2, *p_act, *p_k;
  if (!init) {
    cudaDriverEntryPointQueryResult qr;
    void* fn = nullptr;
    cudaGetDriverEntryPoint("cuTensorMapEncodeTiled", &fn, cudaEnableDefault, &qr);
    s_encode = (EncodeFn)fn;
    p_h = sym_addr(g_h); p_o = sym_addr(g_o); p_x1 = sym_addr(g_x1); p_h2 = sym_addr(g_h2); p_act = sym_addr(g_act); p_k = sym_addr(g_k);
    cudaFuncSetAttribute(GK_QKV, cudaFuncAttributeMaxDynamicSharedMemorySize, SM_QKV);
    cudaFuncSetAttribute(GK_RES, cudaFuncAttributeMaxDynamicSharedMemorySize, SM_RES);
    cudaFuncSetAttribute(GK_RES64, cudaFuncAttributeMaxDynamicSharedMemorySize, SM_RES64);
    cudaFuncSetAttribute(GK_RESB, cudaFuncAttributeMaxDynamicSharedMemorySize, SM_RESB);
    cudaFuncSetAttribute(GK_PART, cudaFuncAttributeMaxDynamicSharedMemorySize, SM_PART);
    cudaFuncSetAttribute(attn_kernel, cudaFuncAttributeMaxDynamicSharedMemorySize, ATT_LSMEM);
    cudaFuncSetAttribute(GK_GLU, cudaFuncAttributeMaxDynamicSharedMemorySize, SM_GLU);
    cudaFuncSetAttribute(rec_kernel, cudaFuncAttributeMaxDynamicSharedMemorySize, rc::SMEM);
    cudaFuncAttributes fa;
    cudaFuncGetAttributes(&fa, mod_kernel); cudaFuncGetAttributes(&fa, ln_kernel); cudaFuncGetAttributes(&fa, attn_kernel);
    cudaFuncGetAttributes(&fa, rec_kernel); cudaFuncGetAttributes(&fa, GK_QKV);
    cudaFuncGetAttributes(&fa, GK_RES); cudaFuncGetAttributes(&fa, GK_GLU);
    int lo = 0, hi = 0;
    cudaDeviceGetStreamPriorityRange(&lo, &hi);
    cudaStreamCreateWithPriority(&s_rec, cudaStreamNonBlocking, hi);
    cudaStreamCreateWithPriority(&s_att, cudaStreamNonBlocking, lo);
    cudaEventCreateWithFlags(&s_evFork2, cudaEventDisableTiming);
    cudaEventCreateWithFlags(&s_evJoin2, cudaEventDisableTiming);
    cudaEventCreateWithFlags(&s_evJoin3, cudaEventDisableTiming);
    cudaFuncGetAttributes(&fa, GK_RES64);
    cudaFuncGetAttributes(&fa, gate_kernel);
    cudaFuncSetAttribute(gate_kernel, cudaFuncAttributePreferredSharedMemoryCarveout, 100);
    cudaFuncSetAttribute(GK_QKV, cudaFuncAttributePreferredSharedMemoryCarveout, 100);
    cudaFuncSetAttribute(GK_RES, cudaFuncAttributePreferredSharedMemoryCarveout, 100);
    cudaFuncSetAttribute(GK_RES64, cudaFuncAttributePreferredSharedMemoryCarveout, 100);
    cudaFuncSetAttribute(GK_GLU, cudaFuncAttributePreferredSharedMemoryCarveout, 100);
    cudaFuncSetAttribute(attn_kernel, cudaFuncAttributePreferredSharedMemoryCarveout, 100);
    cudaFuncSetAttribute(ln_kernel, cudaFuncAttributePreferredSharedMemoryCarveout, 100);
    cudaFuncSetAttribute(mod_kernel, cudaFuncAttributePreferredSharedMemoryCarveout, 100);
    cudaEventCreateWithFlags(&s_evFork, cudaEventDisableTiming);
    cudaEventCreateWithFlags(&s_evJoin, cudaEventDisableTiming);
    {
      cudaLaunchConfig_t cfg = {};
      cfg.gridDim = dim3(rc::NCTA); cfg.blockDim = dim3(384); cfg.dynamicSmemBytes = rc::SMEM;
      cudaLaunchAttribute at[1];
      at[0].id = cudaLaunchAttributeClusterDimension;
      at[0].val.clusterDim.x = 3; at[0].val.clusterDim.y = 1; at[0].val.clusterDim.z = 1;
      cfg.attrs = at; cfg.numAttrs = 1;
      int ncl = 0, nsm = 0;
      cudaDeviceGetAttribute(&nsm, cudaDevAttrMultiProcessorCount, 0);
      if (cudaOccupancyMaxActiveClusters(&ncl, rec_kernel, &cfg) != cudaSuccess) { ncl = 0; (void)cudaGetLastError(); }
      s_fallback = (ncl < 32 || nsm < rc::NCTA + SHADOW_CTAS) ? 1 : 0;
    }
    init = true;
  }
  CUtensorMap mA_h = make_map(p_h, DM, S_TOK, 64, 128);
  CUtensorMap mB_q = make_map(Wq, HD, DM, 64, 64), mB_k = make_map(Wk, HD, DM, 64, 64), mB_v = make_map(Wv, HD, DM, 64, 64);
  CUtensorMap mA_o = make_map(p_o, HD, S_TOK, 64, 128), mB_o = make_map(Wo, DM, HD, 64, 64);
  CUtensorMap mA_o64 = make_map(p_o, HD, S_TOK, 64, 64);
  CUtensorMap mA_h2 = make_map(p_h2, DM, S_TOK, 64, 128);
  CUtensorMap mB_g = make_map(w_gate, FF, DM, 64, 64), mB_u = make_map(w_up, FF, DM, 64, 64);
  CUtensorMap mA_act = make_map(p_act, FF, S_TOK, 64, 128), mB_d = make_map(w_down, DM, FF, 64, 64);

  cudaStream_t st = cudaStreamPerThread;
  if (s_fallback) {
    mod_kernel<<<120, 256, 0, st>>>(cvec, w_mod);
    ln_kernel<<<S_TOK / 8, 256, 0, st>>>(x, (bf16*)p_h, 0, DM, 0u, 0, nullptr);
    GemmP p{16, 48, 10, 0, nullptr, nullptr, 0, 2, 1, 16, 0};
    launch_gemm(GK_QKV, 64, 288, SM_QKV, st, 0, mA_h, mB_q, mB_k, mB_v, p);
    fb_init<<<1, 256, 0, st>>>(mem0);
    for (int s = 0; s < NSEG; s++) {
      fb_qkv<<<96, 128, 0, st>>>(Wq, Wk, Wv, s);
      if (s < NSEG - 1) { fb_attn<<<NH, 128, 0, st>>>(s); fb_wo<<<20, 256, 0, st>>>(Wo); }
    }
    attn_kernel<<<NH * NSEG / 2, 128, ATT_LSMEM, st>>>(0);
  } else {
  mod_kernel<<<120, 256, 0, st>>>(cvec, w_mod);
  cudaEventRecord(s_evFork, st);
  ln_kernel<<<S_TOK / 8, 256, 0, st>>>(x, (bf16*)p_h, 0, DM, rc::NCTA, 0, nullptr);
  cudaEventRecord(s_evFork2, st);
  {
    GemmP p{16, 48, 10, 0, nullptr, nullptr, 0, 2, 1, 16, 0};
    launch_gemm(GK_QKV, SHADOW_CTAS, 288, SM_QKV, st, MC_QKV, mA_h, mB_q, mB_k, mB_v, p);
  }
  cudaStreamWaitEvent(s_rec, s_evFork, 0);
  rec_kernel<<<rc::NCTA, 384, rc::SMEM, s_rec>>>(Wq, Wk, Wv, Wo, mem0);
  cudaEventRecord(s_evJoin, s_rec);
  cudaStreamWaitEvent(s_att, s_evFork2, 0);
  gate_kernel<<<1, 1, 0, s_att>>>(SHADOW_CTAS);
  attn_kernel<<<NH * NSEG / 2, 128, ATT_LSMEM, s_att>>>(0);
  cudaEventRecord(s_evJoin2, s_att);
  cudaStreamWaitEvent(st, s_evJoin, 0);
  cudaStreamWaitEvent(st, s_evJoin2, 0);
  }

  {
    GemmP p{16, 5, 64, 0, x, (bf16*)p_x1, 2 * DM, 0, 0, 0, 0};
    launch_gemm(GK_RESB, 80, 288, SM_RESB, st, MC_POST, mA_o, mB_o, mB_o, mB_o, p);
  }
  {
    cudaLaunchConfig_t cfg = {};
    cfg.gridDim = dim3(S_TOK / 8); cfg.blockDim = dim3(256); cfg.stream = st;
    cudaLaunchAttribute at[1];
    at[0].id = cudaLaunchAttributeProgrammaticStreamSerialization;
    at[0].val.programmaticStreamSerializationAllowed = 1;
    cfg.attrs = at; cfg.numAttrs = USE_PDL;
    cudaLaunchKernelEx(&cfg, ln_kernel, WO_SPLITK ? x : (const bf16*)p_x1, (bf16*)p_h2, 3 * DM, 4 * DM, 0u, 1, WO_SPLITK ? (bf16*)p_x1 : (bf16*)nullptr);
  }
  {
    GemmP p{16, 27, 10, 0, nullptr, nullptr, 0, 0, 0, 0, 0};
    launch_gemm(GK_GLU, 264, 288, SM_GLU, st, MC_POST, mA_h2, mB_g, mB_u, mB_u, p, USE_PDL);
  }
  {
    GemmP p{16, 5, 27, 0, (const bf16*)p_x1, out, 5 * DM, 0, 0, 0, 0};
    launch_gemm(GK_RESB, 80, 288, SM_RESB, st, MC_POST, mA_act, mB_d, mB_d, mB_d, p, USE_PDL);
  }
}
```
